```python
import torch

def _softmax(x, axis=-1):
    return torch.softmax(x, dim=axis)
def _gelu(x):
    return torch.nn.functional.gelu(x, approximate="tanh")
def _silu(x):
    return torch.nn.functional.silu(x)
def _sigmoid(x):
    return torch.sigmoid(x)
def _layernorm(x, axis=-1, eps=1e-5):
    m = x.mean(dim=axis, keepdim=True)
    v = x.var(dim=axis, keepdim=True, unbiased=False)
    return (x - m) / torch.sqrt(v + eps)
def _scatter_add(tgt, idx, src, axis=0):
    return tgt.clone().index_add_(axis, idx, src)
def _segment_sum(src, seg, n):
    out = torch.zeros((n,) + src.shape[1:], dtype=src.dtype)
    return out.index_add_(0, seg, src)
def _pad(x, pw):
    flat = tuple(v for pair in reversed(pw) for v in pair)
    return torch.nn.functional.pad(x, flat)

kernel_name = 'concat_heads__ssm_conv_s4__ssm_conv_h3__prompt'

def setup_inputs():

    _w = (lambda a: (lambda t: t.to(torch.bfloat16) if t.is_floating_point() else t)(torch.as_tensor(a)))
    def _A_setup():
        B, L, D, N = 1, 2048, 576, 128
        A_re = -(lambda _x: torch.exp(torch.as_tensor(_x)))((lambda *s: torch.randn(*s, dtype=torch.bfloat16) * 6.4)(D, N))
        A_im = torch.pi * (lambda *s: torch.randn(*s, dtype=torch.bfloat16) * 0.05)(D, N)
        B_re = (lambda *s: torch.randn(*s, dtype=torch.bfloat16) * 0.1)(D, N)
        B_im = (lambda *s: torch.randn(*s, dtype=torch.bfloat16) * 0.1)(D, N)
        C_re = (lambda *s: torch.randn(*s, dtype=torch.bfloat16) * 0.1)(D, N)
        C_im = (lambda *s: torch.randn(*s, dtype=torch.bfloat16) * 0.1)(D, N)
        log_dt = (lambda *s: torch.randn(*s, dtype=torch.bfloat16) * 0.05)(D) * 0.5 - 4.0
        Dskip = (lambda *s: torch.randn(*s, dtype=torch.bfloat16) * 0.05)(D)
        return {
            "u": _w((lambda *s: torch.randn(*s, dtype=torch.bfloat16) * 0.05)(B, L, D)),
            "A_re": _w(A_re),
            "A_im": _w(A_im),
            "B_re": _w(B_re),
            "B_im": _w(B_im),
            "C_re": _w(C_re),
            "C_im": _w(C_im),
            "log_dt": _w(log_dt),
            "Dskip": _w(Dskip),
        }
    _A_in = _A_setup()

    def _B_setup():
        B, S, D = 1, 2048, 576
        ks = 4
        return {
            "q": _w((lambda *s: torch.randn(*s, dtype=torch.bfloat16) * 0.05)(B, S, D)),
            "k": _w((lambda *s: torch.randn(*s, dtype=torch.bfloat16) * 0.4)(B, S, D)),
            "v": _w((lambda *s: torch.randn(*s, dtype=torch.bfloat16) * 0.4)(B, S, D)),
            "shift_k": _w((lambda *s: torch.randn(*s, dtype=torch.bfloat16) * 0.4)(D, ks) * 0.5),
            "ssm_k": _w((lambda *s: torch.randn(*s, dtype=torch.bfloat16) * 0.4)(D, S) * (1.0 / S ** 0.5)),
            "ssm_D": _w((lambda *s: torch.randn(*s, dtype=torch.bfloat16) * 0.4)(D)),
        }
    _B_in = _B_setup()

    return {
        "A_u": _A_in["u"],
        "A_A_re": _A_in["A_re"],
        "A_A_im": _A_in["A_im"],
        "A_B_re": _A_in["B_re"],
        "A_B_im": _A_in["B_im"],
        "A_C_re": _A_in["C_re"],
        "A_C_im": _A_in["C_im"],
        "A_log_dt": _A_in["log_dt"],
        "A_Dskip": _A_in["Dskip"],
        "B_q": _B_in["q"],
        "B_k": _B_in["k"],
        "B_v": _B_in["v"],
        "B_shift_k": _B_in["shift_k"],
        "B_ssm_k": _B_in["ssm_k"],
        "B_ssm_D": _B_in["ssm_D"],
    }

def reference(A_u, A_A_re, A_A_im, A_B_re, A_B_im, A_C_re, A_C_im, A_log_dt, A_Dskip, B_q, B_k, B_v, B_shift_k, B_ssm_k, B_ssm_D):
    def _A_ref(u, A_re, A_im, B_re, B_im, C_re, C_im, log_dt, Dskip):
        Bsz, L, D = u.shape
        dt = torch.exp(log_dt)[:, None]
        A = A_re + 1j * A_im
        Bc = B_re + 1j * B_im
        Cc = C_re + 1j * C_im
        logdA = dt * A
        dB = dt * Bc
        l = (lambda x, dt: x.to(dt))(torch.arange(L), A_re.dtype)
        P = torch.exp(logdA[:, :, None] * l[None, None, :])
        K = torch.einsum("dn,dnl,dn->dl", Cc, P, dB).real
        L2 = 2 * L
        Kp = _pad(K, ((0, 0), (0, L)))
        up = (lambda x, *d: x.permute(*d))(u, 0, 2, 1)
        up = _pad(up, ((0, 0), (0, 0), (0, L)))
        Kf = (lambda x, axes=(-2,-1): torch.fft.rfft2(x.float(), dim=axes))(Kp[:, None, :], axes=(-2, -1))
        Uf = (lambda x, axes=(-2,-1): torch.fft.rfft2(x.float(), dim=axes))(up[:, :, None, :], axes=(-2, -1))
        Yf = Uf * Kf[None, :, :, :]
        y = (lambda x, s, axes=(-2,-1): torch.fft.irfft2(x, s=s, dim=axes).to(torch.bfloat16))(Yf, (1, L2), axes=(-2, -1))[:, :, 0, :L]
        y = (lambda x, *d: x.permute(*d))(y, 0, 2, 1) + u * Dskip[None, None, :]
        return y

    def _B_ref(q, k, v, shift_k, ssm_k, ssm_D):
        B, S, D = q.shape
        ks = shift_k.shape[-1]
        k_pad = _pad(k, ((0, 0), (ks - 1, 0), (0, 0)))
        k_shift = torch.zeros_like(k)
        for t in range(ks):
            k_shift = k_shift + k_pad[:, t:t + S, :] * shift_k[:, ks - 1 - t][None, None, :]
        kv = k_shift * v
        L = 2 * S
        kv_pad = _pad(kv, ((0, 0), (0, S), (0, 0)))
        kf_pad = _pad(ssm_k, ((0, 0), (0, S)))
        kv_f = (lambda x, axes=(-2,-1): torch.fft.rfft2(x.float(), dim=axes))(kv_pad[:, None, :, :], axes=(1, 2))
        kf_f = (lambda x, axes=(-2,-1): torch.fft.rfft2(x.float(), dim=axes))(kf_pad[:, None, :], axes=(1, 2))
        kf_f = (lambda x, *d: x.permute(*d))(kf_f, 1, 2, 0)
        y_f = kv_f * kf_f[None, :, :, :]
        y = (lambda x, s, axes=(-2,-1): torch.fft.irfft2(x, s=s, dim=axes).to(torch.bfloat16))(y_f, (1, L), axes=(1, 2))[:, 0, :S, :]
        y = y + kv * ssm_D[None, None, :]
        return q * y

    a = _A_ref(A_u, A_A_re, A_A_im, A_B_re, A_B_im, A_C_re, A_C_im, A_log_dt, A_Dskip)
    b = _B_ref(B_q, B_k, B_v, B_shift_k, B_ssm_k, B_ssm_D)
    return torch.concatenate([a, b], axis=-1)
```

```cpp
#include <cuda_runtime.h>
#include <cuda.h>
#include <cuda_bf16.h>
#include <stdint.h>

enum : uint32_t {
    OFF_C = 0,
    OFF_BAR = 5120,
    OFF_X = 6144,
    OFF_H = 55296,
    OFF_K = 104448, KP = 6912,
    OFF_V = 159744, VP = 6528,
    OFF_TAB = 88064, TABP = 10912,
    OFF_U = 175360, UP = 4352,
    SMEM_BYTES = 211968,
    BAR_K = 0, BAR_X = 8, BAR_Y = 16, BAR_PD = 24, BAR_ED = 32, BAR_H = 40, BAR_H2 = 52
};
#define NB_CLUSTERS 12
#define NA_CLUSTERS 18

struct __align__(64) Maps { CUtensorMap k, kh, v, q32, q16, o32, o16, u; };
struct Ptrs {
    const uint16_t *are, *aim, *bre, *bim, *cre, *cim, *logdt, *dskip, *shiftk, *ssmk, *ssmd;
    uint16_t* out;
};

#define MARK(i)
#define MARK_BEGIN()
#define MARK_END()
#define TRACE_BYTES 0

#define OUT_STG 1
#define BDELAY 0
#define ADELAY 1500
#ifndef HIPOS
#define HIPOS 1
#endif
#define WAITMODE 0
#define WAITNS 100
#define DI __device__ __forceinline__
DI uint32_t mapa(uint32_t a, uint32_t r) { uint32_t d; asm("mapa.shared::cluster.u32 %0,%1,%2;" : "=r"(d) : "r"(a), "r"(r)); return d; }
DI void bar_wait(uint32_t bar) {
    uint32_t ok, it = 0;
    do {
        asm volatile("{.reg .pred p; mbarrier.try_wait.parity.shared::cta.b64 p,[%1],0; selp.u32 %0,1,0,p;}" : "=r"(ok) : "r"(bar) : "memory");
        if (++it > (1u << 24)) __trap();
    } while (!ok);
}
DI bool bar_test(uint32_t bar) {
    uint32_t ok;
    asm volatile("{.reg .pred p; mbarrier.test_wait.parity.shared::cta.b64 p,[%1],0; selp.u32 %0,1,0,p;}" : "=r"(ok) : "r"(bar) : "memory");
    return __ballot_sync(0xffffffffu, ok) == 0xffffffffu;
}
DI bool elect() {
    uint32_t p;
    asm volatile("{.reg .pred q; elect.sync _|q,0xffffffff; selp.u32 %0,1,0,q;}" : "=r"(p));
    return p;
}
DI void bar_init(uint32_t bar, uint32_t cnt) { asm volatile("mbarrier.init.shared::cta.b64 [%0],%1;" ::"r"(bar), "r"(cnt) : "memory"); }
DI void bar_expect(uint32_t bar, uint32_t bytes) { asm volatile("mbarrier.arrive.expect_tx.shared::cta.b64 _,[%0],%1;" ::"r"(bar), "r"(bytes) : "memory"); }
DI void init_fence() { asm volatile("fence.mbarrier_init.release.cluster;" ::: "memory"); asm volatile("fence.proxy.async.shared::cta;" ::: "memory"); }
DI bool bar_test1(uint32_t bar) {
    uint32_t ok;
    asm volatile("{.reg .pred p; mbarrier.test_wait.parity.shared::cta.b64 p,[%1],0; selp.u32 %0,1,0,p;}" : "=r"(ok) : "r"(bar) : "memory");
    return ok;
}
DI void bar_arrive(uint32_t bar) { asm volatile("mbarrier.arrive.shared::cta.b64 _,[%0];" ::"r"(bar) : "memory"); }
DI void st_async(uint32_t a, uint32_t bar, uint32_t x, uint32_t y, uint32_t z, uint32_t w) {
    asm volatile("st.async.weak.shared::cluster.mbarrier::complete_tx::bytes.v4.b32 [%0],{%2,%3,%4,%5},[%1];" ::"r"(a), "r"(bar), "r"(x), "r"(y), "r"(z), "r"(w) : "memory");
}
DI void bulk_g2s(uint32_t dst, const void* src, uint32_t bytes, uint32_t bar) {
    asm volatile("cp.async.bulk.shared::cluster.global.mbarrier::complete_tx::bytes [%0],[%1],%2,[%3];" ::"r"(dst), "l"(src), "r"(bytes), "r"(bar) : "memory");
}
DI void tma3(uint32_t dst, const CUtensorMap* m, int c0, int c1, int c2, uint32_t bar) {
    asm volatile("cp.async.bulk.tensor.3d.shared::cluster.global.mbarrier::complete_tx::bytes [%0],[%1,{%3,%4,%5}],[%2];" ::"r"(dst), "l"(m), "r"(bar), "r"(c0), "r"(c1), "r"(c2) : "memory");
}
DI void tma2(uint32_t dst, const CUtensorMap* m, int c0, int c1, uint32_t bar) {
    asm volatile("cp.async.bulk.tensor.2d.shared::cluster.global.mbarrier::complete_tx::bytes [%0],[%1,{%3,%4}],[%2];" ::"r"(dst), "l"(m), "r"(bar), "r"(c0), "r"(c1) : "memory");
}
DI void tma2_st(const CUtensorMap* m, int c0, int c1, uint32_t src) {
    asm volatile("cp.async.bulk.tensor.2d.global.shared::cta.bulk_group [%0,{%2,%3}],[%1];" ::"l"(m), "r"(src), "r"(c0), "r"(c1) : "memory");
}
DI void ldsm4t(uint32_t (&r)[4], uint32_t a) {
    asm volatile("ldmatrix.sync.aligned.m8n8.x4.trans.shared.b16 {%0,%1,%2,%3},[%4];" : "=r"(r[0]), "=r"(r[1]), "=r"(r[2]), "=r"(r[3]) : "r"(a) : "memory");
}
DI uint4 lds128(uint32_t a) { uint4 v; asm volatile("ld.shared.v4.u32 {%0,%1,%2,%3},[%4];" : "=r"(v.x), "=r"(v.y), "=r"(v.z), "=r"(v.w) : "r"(a) : "memory"); return v; }
DI uint2 lds64(uint32_t a) { uint2 v; asm volatile("ld.shared.v2.u32 {%0,%1},[%2];" : "=r"(v.x), "=r"(v.y) : "r"(a) : "memory"); return v; }
DI uint32_t lds32(uint32_t a) { uint32_t v; asm volatile("ld.shared.u32 %0,[%1];" : "=r"(v) : "r"(a) : "memory"); return v; }
DI uint32_t lds16(uint32_t a) { uint32_t v; asm volatile("ld.shared.u16 %0,[%1];" : "=r"(v) : "r"(a) : "memory"); return v; }
DI void sts128(uint32_t a, uint32_t x, uint32_t y, uint32_t z, uint32_t w) { asm volatile("st.shared.v4.u32 [%0],{%1,%2,%3,%4};" ::"r"(a), "r"(x), "r"(y), "r"(z), "r"(w) : "memory"); }
DI void sts64(uint32_t a, uint32_t x, uint32_t y) { asm volatile("st.shared.v2.u32 [%0],{%1,%2};" ::"r"(a), "r"(x), "r"(y) : "memory"); }
DI void sts32(uint32_t a, uint32_t x) { asm volatile("st.shared.u32 [%0],%1;" ::"r"(a), "r"(x) : "memory"); }
DI void sts16(uint32_t a, uint32_t x) { asm volatile("st.shared.u16 [%0],%1;" ::"r"(a), "r"(x) : "memory"); }
DI uint32_t hfma(uint32_t a, uint32_t b, uint32_t c) { uint32_t d; asm("fma.rn.f16x2 %0,%1,%2,%3;" : "=r"(d) : "r"(a), "r"(b), "r"(c)); return d; }
DI uint32_t hfms(uint32_t a, uint32_t b, uint32_t c) { uint32_t d; asm("{.reg .b32 t; neg.f16x2 t,%1; fma.rn.f16x2 %0,t,%2,%3;}" : "=r"(d) : "r"(a), "r"(b), "r"(c)); return d; }
DI uint32_t hmul(uint32_t a, uint32_t b) { uint32_t d; asm("mul.rn.f16x2 %0,%1,%2;" : "=r"(d) : "r"(a), "r"(b)); return d; }
DI uint32_t hadd(uint32_t a, uint32_t b) { uint32_t d; asm("add.rn.f16x2 %0,%1,%2;" : "=r"(d) : "r"(a), "r"(b)); return d; }
DI uint32_t hsub(uint32_t a, uint32_t b) { uint32_t d; asm("sub.rn.f16x2 %0,%1,%2;" : "=r"(d) : "r"(a), "r"(b)); return d; }
DI uint32_t bmul(uint32_t a, uint32_t b) { uint32_t d; asm("mul.rn.bf16x2 %0,%1,%2;" : "=r"(d) : "r"(a), "r"(b)); return d; }
DI uint32_t bfma(uint32_t a, uint32_t b, uint32_t c) { uint32_t d; asm("fma.rn.bf16x2 %0,%1,%2,%3;" : "=r"(d) : "r"(a), "r"(b), "r"(c)); return d; }
DI uint32_t badd(uint32_t a, uint32_t b) { uint32_t d; asm("add.rn.bf16x2 %0,%1,%2;" : "=r"(d) : "r"(a), "r"(b)); return d; }
DI uint32_t bsub(uint32_t a, uint32_t b) { uint32_t d; asm("sub.rn.bf16x2 %0,%1,%2;" : "=r"(d) : "r"(a), "r"(b)); return d; }
DI uint32_t bmaxabs(uint32_t a, uint32_t b) { uint32_t d; asm("max.xorsign.abs.bf16x2 %0,%1,%2;" : "=r"(d) : "r"(a), "r"(b)); return d; }
DI uint32_t cvt_h2(float lo, float hi) { uint32_t d; asm("cvt.rn.f16x2.f32 %0,%1,%2;" : "=r"(d) : "f"(hi), "f"(lo)); return d; }
DI uint32_t cvt_b2(float lo, float hi) { uint32_t d; asm("cvt.rn.bf16x2.f32 %0,%1,%2;" : "=r"(d) : "f"(hi), "f"(lo)); return d; }
DI uint32_t h2_to_b2(uint32_t h) {
    float lo, hi;
    asm("{.reg .b16 l,h; mov.b32 {l,h},%2; cvt.f32.f16 %0,l; cvt.f32.f16 %1,h;}" : "=f"(lo), "=f"(hi) : "r"(h));
    return cvt_b2(lo, hi);
}
DI uint32_t prmt(uint32_t a, uint32_t b, uint32_t s) { uint32_t d; asm("prmt.b32 %0,%1,%2,%3;" : "=r"(d) : "r"(a), "r"(b), "r"(s)); return d; }
DI uint32_t ldg16(const uint16_t* p) { uint32_t v; asm volatile("ld.global.nc.u16 %0,[%1];" : "=r"(v) : "l"(p)); return v; }
DI float blo(uint32_t v) { return __uint_as_float(v << 16); }
DI float bhi(uint32_t v) { return __uint_as_float(v & 0xffff0000u); }

DI void mma_bf(float (&c)[4], const uint32_t* a, uint32_t b0, uint32_t b1, float i0, float i2) {
    asm("mma.sync.aligned.m16n8k16.row.col.f32.bf16.bf16.f32 {%0,%1,%2,%3},{%4,%5,%6,%7},{%8,%9},{%10,%11,%12,%11};"
        : "=f"(c[0]), "=f"(c[1]), "=f"(c[2]), "=f"(c[3]) : "r"(a[0]), "r"(a[1]), "r"(a[2]), "r"(a[3]), "r"(b0), "r"(b1), "f"(i0), "f"(0.f), "f"(i2));
}
DI void mma_h_z(uint32_t& d0, uint32_t& d1, const uint32_t* a, uint32_t b0, uint32_t b1) {
    asm("mma.sync.aligned.m16n8k16.row.col.f16.f16.f16.f16 {%0,%1},{%2,%3,%4,%5},{%6,%7},{%8,%8};"
        : "=r"(d0), "=r"(d1) : "r"(a[0]), "r"(a[1]), "r"(a[2]), "r"(a[3]), "r"(b0), "r"(b1), "r"(0));
}
DI void mma_h(uint32_t& d0, uint32_t& d1, const uint32_t* a, uint32_t b0, uint32_t b1) {
    asm("mma.sync.aligned.m16n8k16.row.col.f16.f16.f16.f16 {%0,%1},{%2,%3,%4,%5},{%6,%7},{%0,%1};"
        : "+r"(d0), "+r"(d1) : "r"(a[0]), "r"(a[1]), "r"(a[2]), "r"(a[3]), "r"(b0), "r"(b1));
}
DI void mma_hf_z(float* c, const uint32_t* a, uint32_t b0, uint32_t b1) {
    asm("mma.sync.aligned.m16n8k16.row.col.f32.f16.f16.f32 {%0,%1,%2,%3},{%4,%5,%6,%7},{%8,%9},{%10,%10,%10,%10};"
        : "=f"(c[0]), "=f"(c[1]), "=f"(c[2]), "=f"(c[3]) : "r"(a[0]), "r"(a[1]), "r"(a[2]), "r"(a[3]), "r"(b0), "r"(b1), "f"(0.f));
}
DI void mma_hf(float* c, const uint32_t* a, uint32_t b0, uint32_t b1) {
    asm("mma.sync.aligned.m16n8k16.row.col.f32.f16.f16.f32 {%0,%1,%2,%3},{%4,%5,%6,%7},{%8,%9},{%0,%1,%2,%3};"
        : "+f"(c[0]), "+f"(c[1]), "+f"(c[2]), "+f"(c[3]) : "r"(a[0]), "r"(a[1]), "r"(a[2]), "r"(a[3]), "r"(b0), "r"(b1));
}
template <int N> DI void ldq(uint32_t (&r)[N], uint32_t addr) {
#pragma unroll
    for (int i = 0; i < N / 4; i++) { uint4 v = lds128(addr + i * 512); r[4 * i] = v.x; r[4 * i + 1] = v.y; r[4 * i + 2] = v.z; r[4 * i + 3] = v.w; }
}

DI void rotp(uint32_t& re, uint32_t& im, uint32_t t, uint32_t s) { re = hfma(t, im, re); im = hfma(s, re, im); re = hfma(t, im, re); }
DI void rotm(uint32_t& re, uint32_t& im, uint32_t t, uint32_t s) { re = hfms(t, im, re); im = hfms(s, re, im); re = hfms(t, im, re); }
template <bool SKIP>
DI void fwd1(const uint32_t (&b)[4], const uint32_t (&F1)[8], const uint32_t (&tw)[4], uint32_t (&z)[8], float dsk = 0.f) {
    uint32_t e0 = badd(b[0], b[2]), e1 = badd(b[1], b[3]), o0 = bsub(b[0], b[2]), o1 = bsub(b[1], b[3]);
#pragma unroll
    for (int mu = 0; mu < 2; mu++) {
        float ce[4], co[4];
        float i0 = SKIP ? blo(F1[4 * mu]) * dsk : 0.f, i2 = SKIP ? blo(F1[4 * mu + 1]) * dsk : 0.f;
        mma_bf(ce, &F1[4 * mu], e0, e1, i0, i2);
        mma_bf(co, &F1[4 * mu], o0, o1, i0, i2);
        uint32_t p = cvt_h2(ce[0], ce[1]), u = cvt_h2(ce[2], ce[3]), r = cvt_h2(co[0], co[1]), q = cvt_h2(co[2], co[3]);
        rotp(p, q, tw[mu], tw[2 + mu]);
        rotp(r, u, tw[mu], tw[2 + mu]);
        z[mu] = p; z[2 + mu] = q; z[4 + mu] = r; z[6 + mu] = u;
    }
}
DI void fwd2(const uint32_t (&z)[8], const uint32_t (&S)[8], uint32_t (&o)[8]) {
    mma_h_z(o[0], o[1], &z[0], S[0], S[1]); mma_h_z(o[2], o[3], &z[0], S[2], S[3]);
    mma_h_z(o[4], o[5], &z[4], S[4], S[5]); mma_h_z(o[6], o[7], &z[4], S[6], S[7]);
}
DI void inv1(const uint32_t (&d)[8], const uint32_t (&iA)[8], const uint32_t (&itw)[4], uint32_t (&z)[8]) {
#pragma unroll
    for (int h = 0; h < 2; h++) {
        mma_h_z(z[2 * h], z[2 * h + 1], &iA[0], hadd(d[h], d[2 + h]), hsub(d[4 + h], d[6 + h]));
        mma_h_z(z[4 + 2 * h], z[5 + 2 * h], &iA[4], hadd(d[4 + h], d[6 + h]), hsub(d[h], d[2 + h]));
        rotp(z[2 * h], z[4 + 2 * h], itw[h], itw[2 + h]);
        rotm(z[2 * h + 1], z[5 + 2 * h], itw[h], itw[2 + h]);
    }
}
template <bool FIRST>
DI void cmac(uint32_t (&d)[8], const uint32_t (&g)[8], const uint32_t (&x)[8]) {
#pragma unroll
    for (int i = 0; i < 4; i++) {
        uint32_t re = FIRST ? hmul(g[i], x[i]) : hfma(g[i], x[i], d[i]);
        uint32_t im = FIRST ? hmul(g[i], x[4 + i]) : hfma(g[i], x[4 + i], d[4 + i]);
        d[i] = hfms(g[4 + i], x[4 + i], re);
        d[4 + i] = hfma(g[4 + i], x[i], im);
    }
}
DI uint32_t warp_maxexp(uint32_t m) {
    m &= 0x7fff7fffu;
    m = max(m & 0xffffu, m >> 16);
    m = __reduce_max_sync(0xffffffffu, m) >> 7;
    return min(max(m, 20u), 234u);
}

template <int D0>
DI void h_blocks(uint32_t (&hb)[4][4], const uint32_t (&F1)[8], const uint32_t (&tw)[4], const uint32_t (&S)[8], uint32_t (&G)[4][8], uint32_t (&Hp)[8],
                 uint32_t gsp, float dsk) {
#pragma unroll
    for (int d = 0; d < 4; d++) { hb[d][2] = __shfl_xor_sync(0xffffffffu, hb[d][2], 28); hb[d][3] = __shfl_xor_sync(0xffffffffu, hb[d][3], 28); }
#pragma unroll
    for (int d = 0; d < 4; d++) {
        uint32_t z[8], H[8], T[8];
        if (D0 + d == 0) fwd1<true>(hb[d], F1, tw, z, dsk); else fwd1<false>(hb[d], F1, tw, z);
        fwd2(z, S, H);
        uint32_t(&o)[8] = D0 == 0 ? G[d] : T;
#pragma unroll
        for (int i = 0; i < 4; i++) {
            o[i] = D0 + d ? hadd(H[i], Hp[4 + i]) : H[i];
            o[4 + i] = D0 + d ? hsub(H[4 + i], Hp[i]) : H[4 + i];
        }
#pragma unroll
        for (int i = 0; i < 8; i++) Hp[i] = H[i];
        if (D0) { sts128(gsp + d * 1024, o[0], o[1], o[2], o[3]); sts128(gsp + d * 1024 + 512, o[4], o[5], o[6], o[7]); }
    }
}

DI void conv_channel(uint32_t sb, uint32_t hbase, uint32_t xaddr, uint32_t xpitch, uint32_t ydst, uint32_t ybar, uint32_t ypitch, float dskip, int eadj,
                     uint32_t hmax, const uint16_t* hsrc, uint32_t hbar) {
    const uint32_t lane = threadIdx.x & 31;
    const uint32_t frag = sb + OFF_C + lane * 16, gsp = hbase + lane * 16;
    const uint32_t haddr = hbase + (lane & 15) * 32 + (lane >> 4) * 16;
    uint32_t F1[8], tw[4], S[8], G[4][8], Hp[8];
    uint32_t eh = 0;
    int seen = 0, first = 0;
    bool need_h = true;
    for (;;) {
        ldq(F1, frag); ldq(tw, frag + 2 * 512); ldq(S, frag + 3 * 512);
        if (need_h) {
            uint32_t hb[4][4];
#pragma unroll
            for (int d = 0; d < 4; d++) ldsm4t(hb[d], haddr + d * 512);
            uint32_t m0 = bmaxabs(hmax, cvt_b2(dskip * 0.0625f, 0.f)), m1 = bmaxabs(hb[0][0], hb[0][1]);
#pragma unroll
            for (int i = 2; i < 16; i += 2) { m0 = bmaxabs(m0, hb[i >> 2][i & 3]); m1 = bmaxabs(m1, hb[i >> 2][(i & 3) + 1]); }
            eh = warp_maxexp(bmaxabs(m0, m1));
#pragma unroll
            for (int i = 0; i < 8; i++) F1[i] = bmul(F1[i], (254u - eh) * 0x00800080u);
            h_blocks<0>(hb, F1, tw, S, G, Hp, gsp, (lane & 3) ? 0.f : dskip);
            MARK(3);
            if (first == 0) {
                if (hsrc && elect()) bulk_g2s(hbase + 2048, hsrc + 1024, 2048, hbar);
                __syncwarp();
                asm volatile("barrier.cluster.wait.aligned;" ::: "memory");
                bar_wait(sb + OFF_BAR + BAR_X * 8);
            }
            MARK(4);
        }
        uint32_t iA[8], itw[4], G1[8];
        uint32_t oscale, xs;
        uint32_t X[4][8], D[5][8], Dn[8], Xr[2][8];
        uint32_t xa = xaddr, ya = ydst, yb = ybar;
        {
            uint32_t b[4], z[8], m = 0;
#pragma unroll 1
            for (int i = seen; i >= 0; i--) {
                ldsm4t(b, xaddr + i * xpitch);
                m = bmaxabs(bmaxabs(bmaxabs(b[0], b[1]), bmaxabs(b[2], b[3])), m);
            }
            ldq(F1, frag); ldq(iA, frag + 5 * 512); ldq(itw, frag + 7 * 512); ldq(G1, frag + 8 * 512);
            uint32_t ex = warp_maxexp(m);
            xs = (254u - ex) * 0x00800080u;
#pragma unroll
            for (int i = 0; i < 8; i++) F1[i] = bmul(F1[i], xs);
            oscale = (uint32_t)min(max((int)(ex + eh) - 127 + eadj, 1), 254) * 0x00800080u;
            fwd1<false>(b, F1, tw, z);
            fwd2(z, S, X[0]);
            cmac<true>(D[0], G[0], X[0]);
        }
        bool redo = false;
#pragma unroll
        for (int j = 0; j < 8; j++) {
            uint32_t(&dj)[8] = j < 4 ? D[0] : D[j - 3];
            uint32_t(&xj)[8] = j < 4 ? X[j] : Xr[j & 1];
            uint32_t(&xn)[8] = j + 1 < 4 ? X[j + 1] : Xr[(j + 1) & 1];
            uint32_t(&dn)[8] = j + 1 < 4 ? Dn : D[j + 1 - 3 < 5 ? j + 1 - 3 : 4];
            if (j == HIPOS && need_h) {
                uint32_t hb[4][4];
                if (hsrc) bar_wait(hbar);
#pragma unroll
                for (int d = 0; d < 4; d++) ldsm4t(hb[d], haddr + 2048 + d * 512);
                ldq(F1, frag);
#pragma unroll
                for (int i = 0; i < 8; i++) F1[i] = bmul(F1[i], (254u - eh) * 0x00800080u);
                h_blocks<4>(hb, F1, tw, S, G, Hp, gsp, 0.f);
                ldq(F1, frag);
#pragma unroll
                for (int i = 0; i < 8; i++) F1[i] = bmul(F1[i], xs);
                        }
            if (j == 3) {
                cmac<true>(D[1], G[2], X[2]); cmac<false>(D[1], G[3], X[1]);
                cmac<true>(D[2], G[3], X[2]);
#pragma unroll
                for (int dl = 4; dl < 8; dl++) {
                    uint32_t T[8];
                    ldq(T, gsp + (dl - 4) * 1024);
#pragma unroll
                    for (int i = 7 - dl; i >= 0; i--) {
                        if (dl == 4 && i >= 2) cmac<true>(D[dl + i - 3], T, X[i]); else cmac<false>(D[dl + i - 3], T, X[i]);
                    }
                }
                ldq(F1, frag); ldq(tw, frag + 2 * 512); ldq(S, frag + 3 * 512); ldq(iA, frag + 5 * 512); ldq(itw, frag + 7 * 512); ldq(G1, frag + 8 * 512);
#pragma unroll
                for (int i = 0; i < 8; i++) F1[i] = bmul(F1[i], xs);
            }
            uint32_t b[4], zf[8], zi[8]; float y[8];
            if (j < 7) { bar_wait(sb + OFF_BAR + (BAR_X + j + 1) * 8); xa += xpitch; asm volatile("" : "+r"(xa)); ldsm4t(b, xa); }
            inv1(dj, iA, itw, zi);
            if (j < 7) fwd1<false>(b, F1, tw, zf);
            if (j < 3) { cmac<true>(dn, G[j + 1], X[0]); if (j == 2) cmac<false>(dn, G[2], X[1]); }
            else if (j < 7) { cmac<false>(dn, G[1], xj); if (j + 3 < 8) cmac<false>(D[j + 3 - 3], G[3], xj); }
            mma_hf_z(&y[0], &zi[0], G1[0], G1[1]); mma_hf_z(&y[4], &zi[0], G1[2], G1[3]);
            mma_hf(&y[0], &zi[4], G1[4], G1[5]); mma_hf(&y[4], &zi[4], G1[6], G1[7]);
            if (j < 7) fwd2(zf, S, xn);
            if (j >= 1 && j < 3) cmac<false>(dn, G[1], xj);
            if (j >= 3 && j + 2 < 8) cmac<false>(D[j + 2 - 3], G[2], xj);
            uint32_t o0 = bmul(cvt_b2(y[0], y[2]), oscale), o1 = bmul(cvt_b2(y[1], y[3]), oscale);
            uint32_t o2 = bmul(cvt_b2(y[4], y[6]), oscale), o3 = bmul(cvt_b2(y[5], y[7]), oscale);
            if (j < 7) {
                cmac<false>(dn, G[0], xn);
                if (j + 1 < 4) {
#pragma unroll
                    for (int i = 0; i < 8; i++) D[0][i] = Dn[i];
                }
            }
            if (j >= HIPOS && (j > seen || hsrc) && __any_sync(0xffffffffu, !(fabsf(y[0]) <= 3.0e38f))) { seen = j; first = j; redo = true; break; }
            if (j >= first) st_async(ya, yb, o0, o1, o2, o3);
            ya += ypitch; yb += 8; asm volatile("" : "+r"(ya), "+r"(yb));
            MARK(5 + j);
        }
        if (!redo) break;
        need_h = hsrc != nullptr;
        if (need_h) {
            __syncwarp();
#pragma unroll 1
            for (int i = 0; i < 8; i++) {
                uint4 v = __ldg((const uint4*)hsrc + i * 32 + lane);
                sts128(gsp + i * 512, v.x, v.y, v.z, v.w);
                hmax = bmaxabs(bmaxabs(bmaxabs(v.x, v.y), bmaxabs(v.z, v.w)), hmax);
            }
            __syncwarp();
            hsrc = nullptr;
        }
    }
}

struct Cx { uint32_t r, i; };
DI Cx cmul(Cx a, Cx b) { Cx d; d.r = hfms(a.i, b.i, hmul(a.r, b.r)); d.i = hfma(a.i, b.r, hmul(a.r, b.i)); return d; }
DI Cx cmulc(Cx a, Cx b) { Cx d; d.r = hfma(a.i, b.i, hmul(a.r, b.r)); d.i = hfms(a.r, b.i, hmul(a.i, b.r)); return d; }
DI void cexpf_(float a2, float b, float l, float& re, float& im) {
    float m, t = b * l;
    asm("ex2.approx.ftz.f32 %0,%1;" : "=f"(m) : "f"(a2 * l));
    re = m * __cosf(t); im = m * __sinf(t);
}
DI void csq(float& re, float& im) { float r = re * re - im * im; im = 2.f * re * im; re = r; }

DI void powers(float a0, float b0, float a1, float b1, Cx (&E)[11]) {
#pragma unroll
    for (int k = 0; k < 3; k++) {
        float r0, i0, r1, i1;
        const float l = k == 0 ? 1.f : k == 1 ? 16.f : 256.f;
        cexpf_(a0, b0, l, r0, i0); cexpf_(a1, b1, l, r1, i1);
        E[4 * k].r = cvt_h2(r0, r1); E[4 * k].i = cvt_h2(i0, i1);
#pragma unroll
        for (int q = 1; q < 4; q++) if (4 * k + q < 11) {
            csq(r0, i0); csq(r1, i1);
            E[4 * k + q].r = cvt_h2(r0, r1); E[4 * k + q].i = cvt_h2(i0, i1);
        }
    }
}
struct Tabs { Cx w[16], x[8], y[8], z[5], e; };
DI void products(const Cx (&E)[11], Cx c, Tabs& T) {
    T.w[0].r = 0x3c003c00u; T.w[0].i = 0; T.w[1] = E[3]; T.w[2] = E[4]; T.w[4] = E[5]; T.w[8] = E[6]; T.e = E[7];
    T.w[3] = cmul(T.w[2], T.w[1]); T.w[5] = cmul(T.w[4], T.w[1]); T.w[6] = cmul(T.w[4], T.w[2]); T.w[7] = cmul(T.w[4], T.w[3]);
#pragma unroll
    for (int r = 1; r < 8; r++) T.w[8 + r] = cmul(T.w[r], E[6]);
    T.x[0] = c; T.x[1] = cmulc(c, E[0]); T.x[2] = cmulc(c, E[1]); T.x[3] = cmulc(T.x[1], E[1]);
#pragma unroll
    for (int r = 0; r < 4; r++) T.x[4 + r] = cmulc(T.x[r], E[2]);
#pragma unroll
    for (int r = 0; r < 4; r++) T.y[r] = cmulc(T.x[2 * r], E[8]);
    T.y[4] = cmulc(c, E[9]); T.y[5] = cmulc(T.x[4], E[9]); T.y[6] = cmulc(T.y[0], E[9]); T.y[7] = cmulc(T.y[2], E[9]);
    T.z[0] = cmulc(c, E[10]); T.z[1] = cmulc(T.y[0], E[10]); T.z[2] = cmulc(T.y[4], E[10]); T.z[3] = cmulc(T.y[6], E[10]); T.z[4] = cmulc(T.z[0], E[10]);
}
DI void put_tabs(unsigned char* tab, const Tabs& T) {
    const uint32_t lane = threadIdx.x & 31;
#pragma unroll
    for (int r = 0; r < 8; r++) {
        *(uint4*)(tab + r * 576 + lane * 16) = make_uint4(T.w[r].r, T.w[8 + r].r, T.w[r].i, T.w[8 + r].i);
        *(uint4*)(tab + 4608 + r * 576 + lane * 16) = make_uint4(T.x[r].r, T.x[r].i, T.y[r].r, T.y[r].i);
    }
#pragma unroll
    for (int r = 0; r < 5; r++) *(uint2*)(tab + 9216 + r * 288 + lane * 8) = make_uint2(T.z[r].r, T.z[r].i);
    *(uint2*)(tab + 10656 + lane * 8) = make_uint2(T.e.r, T.e.i);
}
DI void mode_sum(const unsigned char* tab, uint32_t (&acc)[2][3][2]) {
    const uint32_t lane = threadIdx.x & 31, g = lane >> 2, c = lane & 3;
    const unsigned char *rw = tab + g * 576 + c * 16, *rz = tab + 9216 + min(g, 4u) * 288 + c * 8, *re = tab + 10656 + c * 8;
#pragma unroll
    for (int k = 0; k < 8; k++) {
        const uint4 wq = *(const uint4*)(rw + k * 64), xq = *(const uint4*)(rw + 4608 + k * 64);
        const uint2 zq = *(const uint2*)(rz + k * 32), eq = *(const uint2*)(re + k * 32);
        uint32_t A0[4] = {wq.x, wq.y, wq.z, wq.w}, A1[4];
        const Cx e = {eq.x, eq.y}, u0 = cmul(Cx{wq.x, wq.z}, e), u1 = cmul(Cx{wq.y, wq.w}, e);
        A1[0] = u0.r; A1[1] = u1.r; A1[2] = u0.i; A1[3] = u1.i;
        mma_h(acc[0][0][0], acc[0][0][1], A0, xq.x, xq.y); mma_h(acc[0][1][0], acc[0][1][1], A0, xq.z, xq.w); mma_h(acc[0][2][0], acc[0][2][1], A0, zq.x, zq.y);
        mma_h(acc[1][0][0], acc[1][0][1], A1, xq.x, xq.y); mma_h(acc[1][1][0], acc[1][1][1], A1, xq.z, xq.w); mma_h(acc[1][2][0], acc[1][2][1], A1, zq.x, zq.y);
    }
}

DI uint32_t gen_kernel(unsigned char* tab, unsigned char* h, const uint2 (&pv)[6], float dt, float& dskip, int& eadj) {
    const uint32_t lane = threadIdx.x & 31, g = lane >> 2, c = lane & 3;
    float a2[4], bb[4], cr[4], ci[4];
    uint32_t mx = 0;
#pragma unroll
    for (int m = 0; m < 4; m++) {
        float v[6];
#pragma unroll
        for (int t = 0; t < 6; t++) { uint32_t w = (m & 2) ? pv[t].y : pv[t].x; v[t] = (m & 1) ? bhi(w) : blo(w); }
        a2[m] = (dt * v[0]) * 1.4426950408889634f; bb[m] = dt * v[1];
        float br = dt * v[2], bi = dt * v[3];
        cr[m] = v[4] * br - v[5] * bi; ci[m] = v[4] * bi + v[5] * br;
        mx = max(mx, max(__float_as_uint(cr[m]) & 0x7fffffffu, __float_as_uint(ci[m]) & 0x7fffffffu));
    }
    const uint32_t ec = min(max(__reduce_max_sync(0xffffffffu, mx) >> 23, 20u), 234u);
    const float sc = __uint_as_float((254u - ec) << 23);
    eadj = (int)ec - 127;
    dskip *= sc;
    MARK(13);
    uint32_t acc[2][3][2];
#pragma unroll
    for (int i = 0; i < 12; i++) acc[i / 6][(i / 2) % 3][i & 1] = 0;
    Cx E[11];
    Tabs T;
    powers(a2[0], bb[0], a2[1], bb[1], E);
    products(E, Cx{cvt_h2(cr[0] * sc, cr[1] * sc), cvt_h2(ci[0] * -sc, ci[1] * -sc)}, T);
    put_tabs(tab, T);
    powers(a2[2], bb[2], a2[3], bb[3], E);
    __syncwarp();
    MARK(14);
    mode_sum(tab, acc);
    products(E, Cx{cvt_h2(cr[2] * sc, cr[3] * sc), cvt_h2(ci[2] * -sc, ci[3] * -sc)}, T);
    __syncwarp();
    MARK(15);
    put_tabs(tab, T);
    __syncwarp();
    mode_sum(tab, acc);
    __syncwarp();
    MARK(16);
    uint32_t hmax = 0;
#pragma unroll
    for (int q = 0; q < 4; q++) {
        const uint32_t r = g + 8 * q, v = h2_to_b2(acc[q >> 1][2][q & 1]);
        *(uint32_t*)(h + r * 16 + c * 4) = h2_to_b2(acc[q >> 1][0][q & 1]);
        *(uint32_t*)(tab + (c < 2 ? 8 * r + 4 * c : 256 + 128 * (c - 2) + 4 * r)) = h2_to_b2(acc[q >> 1][1][q & 1]);
        if (c < 2 || (q == 0 && lane == 2)) { hmax = bmaxabs(hmax, c < 2 ? v : v & 0xffffu); *(uint16_t*)(tab + 512 + 128 * c + 2 * r) = (uint16_t)v; }
        if (c < 2) *(uint16_t*)(tab + 576 + 128 * c + 2 * r) = (uint16_t)(v >> 16);
    }
    __syncwarp();
    const uint2 v1 = *(const uint2*)(tab + lane * 8);
    const uint32_t n1 = *(const uint16_t*)(tab + lane * 8 + 8);
    uint32_t v2[2], n2[2], v3[4], n3[4];
#pragma unroll
    for (int i = 0; i < 2; i++) { v2[i] = *(const uint32_t*)(tab + 256 + (i * 32 + lane) * 4); n2[i] = *(const uint16_t*)(tab + 260 + (i * 32 + lane) * 4); }
#pragma unroll
    for (int i = 0; i < 4; i++) { v3[i] = *(const uint16_t*)(tab + 512 + (i * 32 + lane) * 2); n3[i] = *(const uint16_t*)(tab + 514 + (i * 32 + lane) * 2); }
    *(uint4*)(h + 512 + lane * 16) = make_uint4(prmt(v1.x, 0, 0x1010), prmt(v1.x, v1.y, 0x5432), prmt(v1.y, 0, 0x1010), prmt(v1.y, n1, 0x5432));
#pragma unroll
    for (int i = 0; i < 2; i++) *(uint4*)(h + 1024 + (i * 32 + lane) * 16) = make_uint4(prmt(v2[i], 0, 0x1010), v2[i], prmt(v2[i], 0, 0x3232), prmt(n2[i], 0, 0x1010));
    const uint32_t sel = (lane & 1) ? 0x5454 : 0x5410;
#pragma unroll
    for (int i = 0; i < 4; i++) {
        const uint32_t vv = prmt(v3[i], 0, 0x1010);
        *(uint4*)(h + 2048 + (i * 32 + lane) * 16) = make_uint4(vv, vv, prmt(v3[i], n3[i], sel), prmt(n3[i], 0, 0x1010));
    }
    __syncwarp();
    return hmax;
}

DI void load_raw(const Maps& M, uint32_t sb, bool isB, int ch0, int rank, int s) {
    const int a0 = 16 * s + 4 * rank;
    const uint32_t bar = sb + OFF_BAR + (BAR_K + s) * 8;
    if (isB) {
        tma3(sb + OFF_K + s * KP, &M.kh, ch0, 13, a0 - 1, bar);
        tma3(sb + OFF_K + s * KP + 384, &M.k, ch0, 0, a0, bar);
        tma3(sb + OFF_V + s * VP, &M.v, ch0, 0, a0, bar);
    } else tma3(sb + OFF_U + s * UP, &M.u, ch0, 0, a0, bar);
}
#define START_DELAY 0
#define START_DELAY_A 0
#define LAG 3
#define EARLY_B 1
#define LOOKAHEAD 2
template <int H> DI void send8(const uint32_t (&o)[8], uint32_t dst, uint32_t dst2, uint32_t bar) {
    const int a = H ? 7 : 0, d = H ? -1 : 1;
    st_async(dst, bar, prmt(o[a], o[a + d], 0x5410), prmt(o[a + 2 * d], o[a + 3 * d], 0x5410), prmt(o[a + 4 * d], o[a + 5 * d], 0x5410), prmt(o[a + 6 * d], o[a + 7 * d], 0x5410));
    st_async(dst2, bar, prmt(o[a], o[a + d], 0x7632), prmt(o[a + 2 * d], o[a + 3 * d], 0x7632), prmt(o[a + 4 * d], o[a + 5 * d], 0x7632), prmt(o[a + 6 * d], o[a + 7 * d], 0x7632));
}

DI void make_quad(uint32_t dst, int q) {
    const int lane = threadIdx.x & 31, g = lane >> 2, k0 = 2 * (lane & 3);
    const bool F = q < 2, G = q >= 8, T = q == 2 || q == 7, I = q == 5 || q == 6, lo = q <= 4;
    const int a1 = I ? 128 : (q == 3 || q == 4) ? 64 : 4, a0 = F ? 1 + 32 * q : G ? 1 : T ? -31 : -15 * (a1 >> 1), a3 = (T || G) ? 32 : 0;
    const int U0 = a0 + a1 * (lo ? g : k0), ue = lo ? 0 : a1;
    const int V0 = F ? 15 + 32 * k0 : lo ? 2 * k0 - 15 : I ? g - 15 : G ? 15 + 32 * (4 * (g >> 1) + (g & 1)) : 15 - 2 * g, ve = F ? 32 : lo ? 2 : 0;
    const int v1 = F ? 256 : G ? 64 : 0, d5 = I ? 15 - 2 * g : 0, off = (F || G) ? 1024 - 480 : 1024;
    const uint32_t ph = (F ? 0xcc : T || q == 9 ? 0xff : q == 3 ? 0xc4 : q == 4 ? 0x13 : q == 5 ? 0xf0 : q == 6 ? 0x50 : 0x00);
    uint32_t r[4];
#pragma unroll
    for (int j = 0; j < 4; j++) {
        float v[2];
#pragma unroll
        for (int e = 0; e < 2; e++) {
            const int n = (U0 + e * ue + (j & 1) * a3) * (V0 + e * ve + (j >> 1) * v1 + (j & 1) * d5) + off + (int)((ph >> (2 * j)) & 3) * 512;
            const float x = (float)((n & 2047) - 1024) * 3.0679615757712823e-3f;
            v[e] = __cosf(x);
            if (j < 2) { const float t = __fdividef(v[e], __sinf(x) - 1.f); v[e] = T ? t : v[e]; }
        }
        r[j] = F ? cvt_b2(v[0] * 0.0625f, v[1] * 0.0625f) : cvt_h2(v[0], v[1]);
    }
    sts128(dst + q * 512 + lane * 16, r[0], r[1], r[2], r[3]);
}

__global__ void __cluster_dims__(4, 1, 1) __launch_bounds__(512, 1)
ssm_conv_kernel(const __grid_constant__ Maps M, const Ptrs P) {
    extern __shared__ __align__(1024) unsigned char smem[];
    const uint32_t sb = (uint32_t)__cvta_generic_to_shared(smem);
    const uint32_t w = __shfl_sync(0xffffffffu, threadIdx.x >> 5, 0), lane = threadIdx.x & 31;
    const uint32_t cid = blockIdx.x >> 2, rank = blockIdx.x & 3;
    const bool isB = cid < NB_CLUSTERS;
    const int ch0 = isB ? 48 * cid : 32 * (cid - NB_CLUSTERS);
    const uint32_t bars = sb + OFF_BAR, nch = isB ? 12 : 8;
    MARK_BEGIN();
    if (w < 12) {
        const bool active = w < nch;
        const int ch = ch0 + nch * rank + w;
        const uint32_t hbase = sb + OFF_H + w * 4096;
        uint2 pv[6];
        uint32_t dsk_raw = 0, dt_raw = 0;
        if (isB) {
            if (elect()) {
                bar_init(bars + (BAR_H + w) * 8, 1); bar_init(bars + (BAR_H2 + w) * 8, 1);
                bar_expect(bars + (BAR_H + w) * 8, 2048); bar_expect(bars + (BAR_H2 + w) * 8, 2048);
                init_fence();
                bulk_g2s(hbase, P.ssmk + (size_t)ch * 2048, 2048, bars + (BAR_H + w) * 8);
            }
            __syncwarp();
        } else if (active) {
            const size_t o = (size_t)ch * 128 + lane * 4;
            pv[0] = __ldg((const uint2*)(P.are + o)); pv[1] = __ldg((const uint2*)(P.aim + o)); pv[2] = __ldg((const uint2*)(P.bre + o));
            pv[3] = __ldg((const uint2*)(P.bim + o)); pv[4] = __ldg((const uint2*)(P.cre + o)); pv[5] = __ldg((const uint2*)(P.cim + o));
            dt_raw = ldg16(P.logdt + ch);
        }
        if (active) dsk_raw = ldg16((isB ? P.ssmd : P.dskip) + ch);
        asm volatile("barrier.cluster.arrive.relaxed.aligned;" ::: "memory");
        if (w < 10) make_quad(sb + OFF_C, w);
        asm volatile("setmaxnreg.inc.sync.aligned.u32 152;");
        MARK(2);
        asm volatile("bar.sync 1, 384;" ::: "memory");
        if (active) {
            asm volatile("" : "+r"(dsk_raw), "+r"(dt_raw));
            float dskip = blo(dsk_raw);
            int eadj = 0;
            uint32_t hmax = 0;
            if (isB) bar_wait(bars + (BAR_H + w) * 8);
            else hmax = gen_kernel(smem + OFF_TAB + w * TABP, smem + OFF_H + w * 4096, pv, blo(cvt_b2(expf(blo(dt_raw)), 0.f)), dskip, eadj);
            MARK(1);
            const uint32_t g = lane >> 2, c = lane & 3, cl = nch * rank + w;
            const uint32_t f = cl < 32 ? 2 * (cl >> 3) + (cl & 1) : 4 * ((cl >> 3) & 1) + 2 * (cl & 1);
            const uint32_t yl = (isB ? OFF_K : OFF_U) + cl * 128 + (g ^ f) * 16;
            const uint32_t slot = ((w & 1) * (nch >> 1) + (w >> 1)) ^ (isB ? (lane >> 1) & 3 : lane & 7);
            conv_channel(sb, hbase, sb + OFF_X + lane * nch * 16 + slot * 16, nch * 512, mapa(sb + yl, c), mapa(bars + BAR_Y * 8, c), isB ? KP : UP, dskip, eadj,
                         hmax, isB ? P.ssmk + (size_t)ch * 2048 : nullptr, bars + (BAR_H2 + w) * 8);
        }
    } else {
        const uint32_t iw = w - 12;
        asm volatile("setmaxnreg.dec.sync.aligned.u32 56;");
        {
            const uint32_t b0 = bars + iw * 64;
            if (elect()) {
#pragma unroll
                for (int i = 0; i < 8; i++) bar_init(b0 + i * 8, iw < 3 ? 1 : 3);
            }
            __syncwarp();
            if (iw < 3 && lane < 8) bar_expect(b0 + lane * 8, iw == 0 ? (isB ? KP + VP : UP) : iw == 1 ? nch * 512 : (isB ? 12288 : 4096));
            init_fence();
            __syncwarp();
        }
        asm volatile("barrier.cluster.arrive.relaxed.aligned;" ::: "memory");
        if (iw == 0) {
            { const uint32_t t0 = clock(); while (clock() - t0 < (isB ? BDELAY : ADELAY)) ; }
            if (elect()) { load_raw(M, sb, isB, ch0, rank, 0); load_raw(M, sb, isB, ch0, rank, 1); }
            __syncwarp();
            MARK(20);
            asm volatile("barrier.cluster.wait.aligned;" ::: "memory");
#pragma unroll 1
            for (uint32_t s = 0; s < 8; s++) {
                if (s < 6) {
                    bar_wait(bars + (BAR_K + s) * 8);
                    if (elect()) load_raw(M, sb, isB, ch0, rank, s + 2);
                    __syncwarp();
                }
                if (isB) {
                    bar_wait(bars + (BAR_PD + s) * 8);
                    if (elect()) {
                        const int r0 = 256 * s + 64 * rank;
                        tma2(sb + OFF_V + s * VP, &M.q32, ch0, r0, bars + (BAR_Y + s) * 8);
                        tma2(sb + OFF_V + s * VP + 4096, &M.q16, ch0 + 32, r0, bars + (BAR_Y + s) * 8);
                    }
                    __syncwarp();
                }
            }
        } else if (isB) {
            const uint32_t n = 32 * (iw - 1) + lane, a = n / 24, p = n - 24 * a, dr = p / 6, pl = p - 6 * dr, ag = 4 * rank + a, sw = (ag >> 1) & 3;
            const uint4 t = __ldg((const uint4*)(P.shiftk + (size_t)(ch0 + 2 * p) * 4));
            uint32_t ka = sb + OFF_K + 384 + a * 1632 + p * 4, va = sb + OFF_V + a * 1632 + p * 4;
            uint32_t dst = mapa(sb + OFF_X + ag * 192 + (pl ^ sw) * 16, dr), dst2 = mapa(sb + OFF_X + ag * 192 + ((pl + 6) ^ sw) * 16, dr), bar = mapa(bars + BAR_X * 8, dr);
            const uint4 wt = make_uint4(prmt(t.x, t.z, 0x5410), prmt(t.x, t.z, 0x7632), prmt(t.y, t.w, 0x5410), prmt(t.y, t.w, 0x7632));
            asm volatile("barrier.cluster.wait.aligned;" ::: "memory");
#pragma unroll 1
            for (uint32_t s = 0; s < 8; s++) {
                bar_wait(bars + (BAR_K + s) * 8);
                MARK(1 + s);
                uint32_t k0 = lds32(ka - 4 * 96), k1 = lds32(ka - 3 * 96), k2 = lds32(ka - 2 * 96);
#pragma unroll
                for (int h = 0; h < 2; h++) {
                    uint32_t o[8];
#pragma unroll
                    for (int i = 0; i < 8; i++) {
                        uint32_t k3 = lds32(ka + (8 * h + i) * 96), v = lds32(va + (8 * h + i) * 96);
                        o[i] = bmul(bfma(k3, wt.x, bfma(k2, wt.y, bfma(k1, wt.z, bmul(k0, wt.w)))), v);
                        k0 = k1; k1 = k2; k2 = k3;
                    }
                    if (h) { __syncwarp(); if (lane == 0) bar_arrive(bars + (BAR_PD + s) * 8); }
                    if (h) send8<1>(o, dst + 3072, dst2 + 3072, bar); else send8<0>(o, dst, dst2, bar);
                }
                ka += KP; va += VP; dst += 6144; dst2 += 6144; bar += 8;
            }
        } else {
            asm volatile("barrier.cluster.wait.aligned;" ::: "memory");
#pragma unroll 1
            for (uint32_t s = 0; s < 8; s++) {
                bar_wait(bars + (BAR_K + s) * 8);
                MARK(1 + s);
#pragma unroll 1
                for (uint32_t u = (iw + 2 + 2 * s) % 3; u < 4; u += 3) {
                    const uint32_t h = u & 1, a = (u & 2) + (lane >> 4), p = lane & 15, d = p >> 2, ga = 4 * rank + a;
                    const uint32_t ua = sb + OFF_U + s * UP + a * 1088 + p * 4 + h * 512;
                    const uint32_t dst = mapa(sb + OFF_X + s * 4096 + (16 * h + ga) * 128 + (((p & 3) ^ ga) & 7) * 16, d), bar = mapa(bars + (BAR_X + s) * 8, d);
                    uint32_t o[8];
#pragma unroll
                    for (int i = 0; i < 8; i++) o[i] = lds32(ua + i * 64);
                    if (h) send8<1>(o, dst, dst ^ 64, bar); else send8<0>(o, dst, dst ^ 64, bar);
                }
            }
        }
        MARK(9);
        const uint32_t g = lane >> 2, c = lane & 3, rr = lane & 7, ti = lane >> 3, G = 2 * iw;
        const uint32_t row0 = 16 * (g >> 1) + ((g & 1) ? 15 - G : G), row2 = 16 * (g >> 1) + ((g & 1) ? 15 - G - (c >> 1) : G + (c >> 1));
        const int rd = (g & 1) ? -1 : 1;
        uint32_t ya = sb + (isB ? OFF_K : OFF_U) + (8 * (rr >> 1) + 2 * ti + (rr & 1)) * 128 + (rr ^ G) * 16;
        uint32_t ya2 = sb + OFF_K + (32 + 8 * ((rr >> 1) & 1) + 2 * ti + (rr & 1)) * 128 + ((rr >> 2) ^ (2 * (rr & 3)) ^ G) * 16;
        uint32_t oa = sb + (isB ? OFF_V : OFF_TAB) + row0 * 64 + c * 16, oa2 = sb + OFF_V + 4096 + row2 * 32 + (c & 1) * 16;
        uint4* go = (uint4*)(P.out + (size_t)(64 * rank + row0) * 1152 + (isB ? 576 : 0) + ch0 + c * 8);
        uint4* go2 = (uint4*)(P.out + (size_t)(64 * rank + row2) * 1152 + 576 + ch0 + 32 + (c & 1) * 8);
#pragma unroll 1
        for (uint32_t e = 0; e < 8; e++) {
            bar_wait(bars + (BAR_Y + e) * 8);
            MARK(10 + e);
            uint32_t y0[4], y1[4];
            ldsm4t(y0, ya); ldsm4t(y1, ya ^ 16);
            if (isB) {
                uint32_t y2[4];
                ldsm4t(y2, ya2);
                const uint4 q0 = lds128(oa), q1 = lds128(oa + rd * 64), q2 = lds128(oa2);
                y0[0] = bmul(y0[0], q0.x); y0[1] = bmul(y0[1], q0.y); y0[2] = bmul(y0[2], q0.z); y0[3] = bmul(y0[3], q0.w);
                y1[0] = bmul(y1[0], q1.x); y1[1] = bmul(y1[1], q1.y); y1[2] = bmul(y1[2], q1.z); y1[3] = bmul(y1[3], q1.w);
                *go2 = make_uint4(bmul(y2[0], q2.x), bmul(y2[1], q2.y), bmul(y2[2], q2.z), bmul(y2[3], q2.w));
            }
            go[0] = make_uint4(y0[0], y0[1], y0[2], y0[3]);
            go[rd * 144] = make_uint4(y1[0], y1[1], y1[2], y1[3]);
            go += 256 * 144; go2 += 256 * 144;
            ya += isB ? KP : UP; ya2 += KP; oa += isB ? VP : 4096; oa2 += VP;
        }
    }
    MARK_END();
}

typedef CUresult (*EncodeFn)(CUtensorMap*, CUtensorMapDataType, cuuint32_t, void*, const cuuint64_t*, const cuuint64_t*, const cuuint32_t*,
                             const cuuint32_t*, CUtensorMapInterleave, CUtensorMapSwizzle, CUtensorMapL2promotion, CUtensorMapFloatOOBfill);
static void enc3(EncodeFn f, CUtensorMap* m, void* p, uint32_t b0, uint32_t b1, uint32_t b2) {
    cuuint64_t gd[3] = {576, 16, 128}, gs[2] = {1152, 18432};
    cuuint32_t bd[3] = {b0, b1, b2}, es[3] = {1, 1, 1};
    f(m, CU_TENSOR_MAP_DATA_TYPE_BFLOAT16, 3, p, gd, gs, bd, es, CU_TENSOR_MAP_INTERLEAVE_NONE, CU_TENSOR_MAP_SWIZZLE_NONE,
      CU_TENSOR_MAP_L2_PROMOTION_NONE, CU_TENSOR_MAP_FLOAT_OOB_FILL_NONE);
}
static void enc2(EncodeFn f, CUtensorMap* m, void* p, uint32_t width, uint32_t b0) {
    cuuint64_t gd[2] = {width, 2048}, gs[1] = {(cuuint64_t)width * 2};
    cuuint32_t bd[2] = {b0, 64}, es[2] = {1, 1};
    f(m, CU_TENSOR_MAP_DATA_TYPE_BFLOAT16, 2, p, gd, gs, bd, es, CU_TENSOR_MAP_INTERLEAVE_NONE, CU_TENSOR_MAP_SWIZZLE_NONE,
      CU_TENSOR_MAP_L2_PROMOTION_NONE, CU_TENSOR_MAP_FLOAT_OOB_FILL_NONE);
}

extern "C" void kernel_launch(void* const* d_in, const int* in_sizes, int n_in, void* d_out, int out_size) {
    static EncodeFn enc = nullptr;
    if (!enc) {
        void* fn = nullptr;
        cudaDriverEntryPointQueryResult q;
        cudaGetDriverEntryPoint("cuTensorMapEncodeTiled", &fn, cudaEnableDefault, &q);
        enc = (EncodeFn)fn;
        cudaFuncSetAttribute(ssm_conv_kernel, cudaFuncAttributeMaxDynamicSharedMemorySize, SMEM_BYTES + TRACE_BYTES);
    }
    Maps M;
    enc3(enc, &M.u, d_in[0], 32, 17, 4);
    enc3(enc, &M.k, d_in[10], 48, 17, 4);
    enc3(enc, &M.kh, d_in[10], 48, 4, 1);
    enc3(enc, &M.v, d_in[11], 48, 17, 4);
    enc2(enc, &M.q32, d_in[9], 576, 32);
    enc2(enc, &M.q16, d_in[9], 576, 16);
    enc2(enc, &M.o32, d_out, 1152, 32);
    enc2(enc, &M.o16, d_out, 1152, 16);
    Ptrs P;
    P.are = (const uint16_t*)d_in[1]; P.aim = (const uint16_t*)d_in[2]; P.bre = (const uint16_t*)d_in[3]; P.bim = (const uint16_t*)d_in[4];
    P.cre = (const uint16_t*)d_in[5]; P.cim = (const uint16_t*)d_in[6]; P.logdt = (const uint16_t*)d_in[7]; P.dskip = (const uint16_t*)d_in[8];
    P.shiftk = (const uint16_t*)d_in[12]; P.ssmk = (const uint16_t*)d_in[13]; P.ssmd = (const uint16_t*)d_in[14]; P.out = (uint16_t*)d_out;
    ssm_conv_kernel<<<4 * (NA_CLUSTERS + NB_CLUSTERS), 512, SMEM_BYTES + TRACE_BYTES, cudaStreamPerThread>>>(M, P);
}
```

```cpp
#include <cuda_runtime.h>
#include <cuda.h>
#include <cuda_bf16.h>
#include <stdint.h>

__device__ const __align__(128) uint32_t g_frag[1280] = {
  0x3c763c13,0xbd79bd7d,0x3d5b3d4d,0xbd04bd19,0x3cd93cab,0xbd68bd71,0x3d713d67,0xbcaebcdc,
  0x3d183d03,0xbd4ebd5c,0x3d7d3d78,0xbc19bc7c,0x3d3d3d2b,0xbd2dbd3e,0x3d803d80,0x3b3cbb56,
  0x3d3b3ca5,0xbd2fbd72,0xbd80bd66,0xbb0a3ce2,0x3d793d77,0x3c6abc84,0xbd07bd5e,0xbd5abd00,
  0x3cb43d40,0x3d703d29,0x3cd4bb84,0xbd69bd7f,0xbd15bc07,0x3d503d7e,0x3d7d3d4b,0xbc26bd1c,
  0x3d7c3cfb,0xbc32bd5f,0x3d523d77,0x3d13bc8a,0xbab03d42,0x3d803d27,0xbd393b9d,0x3d313d7f,
  0xbd7abd49,0xbc5d3d1e,0xbd0abd7e,0xbd58bbf4,0x3ccebce8,0xbd6abd64,0x3d6f3c9f,0xbcbabd73,
  0x3d6c3d24,0x3cc8bd44,0xbcc0bd7f,0xbd6d3bb6,0xbd7cbbdb,0x3c3f3d7f,0x3d543d47,0x3d10bd21,
  0x3d37bced,0xbd33bd63,0xbd80bc99,0xba173d74,0xbc513d61,0x3d7b3cf6,0x3d56bc90,0xbd0cbd76,
  0x3d0f3d45,0x3d54bd23,0xbc453d7f,0x3d7b3bc2,0xbcc5bd61,0xbd6c3cf3,0x3cc2bd75,0xbd6dbc93,
  0x3c4b3d75,0x3d7bbc96,0xbd0e3d62,0x3d553cf0,0xb949bd7f,0xbd803bcf,0x3d34bd46,0xbd36bd22,
  0x3a7b3d60,0x3d80bcf8,0x3d32bd76,0xbd38bc8d,0x3d53bd64,0xbd11bcea,0xbd7c3c9c,0xbc383d74,
  0xbd6e3be8,0xbcbd3d7e,0x3ccb3d1f,0x3d6bbd48,0x3c573d43,0x3d7abd25,0x3d0bbd7f,0xbd57bba9,
  0xbd083d73,0x3d59bca2,0xbd7a3d65,0x3c633ce5,0x3d3abc00,0x3d30bd7e,0x3ae23d1d,0x3d80bd4a,
  0x3d51bd7f,0xbd14bb90,0x3d7cbd28,0x3c2cbd41,0xbcd1bc87,0xbd6a3d77,0x3cb7bd5e,0xbd6f3cfe,
  0xbd683d7e,0x3cd7bc0d,0x3d70bd4c,0x3cb1bd1a,0xbd063d3f,0x3d5abd2a,0x3d79bd80,0xbc70bb6f,
  0x3b233c81,0x3d80bd78,0x3d2ebd5d,0xbd3c3d02,0x3d17bca8,0x3d4fbd72,0x3c20bcdf,0xbd7d3d66,
  0xbd7d3d80,0xbc133b3c,0xbd193d2d,0xbd4d3d3d,0xbd713d79,0xbcab3c76,0xbcdc3d04,0xbd673d5b,
  0xbd5c3d68,0xbd033cd9,0xbc7c3cae,0xbd783d71,0xbd3e3d4e,0xbd2b3d18,0xbb563c19,0xbd803d7d,
  0xbd403d79,0xbd293c6a,0x3b84bd07,0x3d7fbd5a,0x3c073cb4,0xbd7e3d70,0xbd4b3cd4,0x3d1cbd69,
  0x3d66bd15,0xbce23d50,0xbd723d7d,0xbca5bc26,0x3d5ebd80,0x3d00bb0a,0xbc843d2f,0xbd773d3b,
  0xbc8a3d6a,0xbd773cce,0x3cfb3cba,0xbd5f3d6f,0x3d7fbd13,0xbb9d3d52,0x3d42bd7c,0x3d273c32,
  0xbbf4bd31,0x3d7ebd39,0xbd493ab0,0x3d1ebd80,0xbd733d58,0xbc9fbd0a,0xbce83d7a,0xbd643c5d,
  0x3c993d54,0xbd743d10,0xbd63bc3f,0x3cedbd7c,0x3c90bd80,0x3d76ba17,0x3cf63d33,0xbd613d37,
  0xbd443d56,0xbd24bd0c,0x3bb6bd7b,0x3d7fbc51,0x3d7fbcc8,0x3bdb3d6c,0xbd213d6d,0xbd47bcc0,
  0x3d453d36,0xbd233d34,0x3d7f3949,0x3bc23d80,0xbd61bd0f,0x3cf3bd54,0xbd753c45,0xbc93bd7b,
  0x3d753cc5,0xbc963d6c,0x3d62bcc2,0x3cf03d6d,0xbd7fbc4b,0x3bcfbd7b,0xbd463d0e,0xbd22bd55,
  0x3d7e3d11,0xbbe83d53,0xbd483c38,0xbd1fbd7c,0xbd253cbd,0xbd43bd6e,0xbba9bd6b,0x3d7f3ccb,
  0xbc8dbd7a,0x3d763c57,0x3d603d57,0xbcf83d0b,0x3d743d38,0xbc9c3d32,0xbd64ba7b,0xbceabd80,
  0x3d653cd1,0x3ce53d6a,0x3ca2bcb7,0x3d733d6f,0x3d1d3d7a,0xbd4abc63,0x3d7e3d59,0xbc003d08,
  0xbd28bae2,0xbd41bd80,0x3b903d30,0xbd7fbd3a,0xbd5ebd7c,0x3cfebc2c,0xbd77bd14,0xbc87bd51,
  0x3d023c70,0x3d5d3d79,0x3c813d06,0xbd78bd5a,0x3d663d3c,0x3cdf3d2e,0xbca8bb23,0xbd72bd80,
  0x3d7e3d7d,0xbc0d3c20,0xbd4cbd17,0xbd1abd4f,0x3d3f3d68,0xbd2abcd7,0xbd80bd70,0xbb6fbcb1,
  0xb9b1baec,0x251b25e4,0x3b8f3beb,0xa91ba9e3,0xb74db89d,0x23122452,0x3a0b3aed,0xa711a852,
  0xb3c1b588,0x1fdb217f,0x375338f1,0xa3dba57f,0xaa17b099,0x16481cb6,0x2e143481,0x9a48a0b6,
  0xb8c7b9ba,0x2e672f65,0x3b0b3b93,0xb257b34c,0xb642b7d7,0x2c6d2d6a,0x396d3a52,0xb067b160,
  0xb2b9b4c6,0x28e92ae1,0x36703862,0xace7aedc,0xa94eaffe,0x1fdb25e4,0x2d4c33df,0xa3dba9e3,
  0xb7e7b8ae,0x31ce32b9,0x3a5a3af9,0xb59fb670,0xb542b68b,0x2ffe30e6,0x38bf399b,0xb3dfb4c9,
  0xb1b4b409,0x2c6d2e34,0x35873796,0xb067b226,0xa885aecd,0x2312294e,0x2c8332b9,0xa711ad4c,
  0xb65fb77a,0x343e34ef,0x39803a23,0xb7eeb881,0xb44cb550,0x31ce3322,0x380238c9,0xb59fb6cc,
  0xb0b2b29f,0x2e67307f,0x34993659,0xb257b469,0xa777ad9c,0x251b2bab,0x2b753191,0xa91bafa4,
  0xb4efb5c1,0x35a43699,0x38813918,0xb905b9a4,0xb2b9b423,0x33a734b8,0x367037c2,0xb73db858,
  0xaf65b133,0x303231e8,0x334c3511,0xb420b5b6,0xa5e4ac6d,0x26ad2d04,0x29e33067,0xaaacb0fd,
  0xb322b423,0x371f3833,0x36cc37c2,0xb9f2ba95,0xb0e6b202,0x34c635eb,0x34c935ce,0xb862b935,
  0xad6aaf98,0x31333357,0x3160337d,0xb511b6f9,0xa452aa7c,0x28202e34,0x28522e78,0xac1fb226,
  0xb07fb133,0x385b3930,0x34693511,0xbab8bb4e,0xae34af98,0x35c1372e,0x3226337d,0xb918b9fa,
  0xaae1acd2,0x32363467,0x2edc30cb,0xb5fdb817,0xa17fa820,0x28e92f65,0x257f2c1f,0xace7b34c,
  0xababac6d,0x39393a4d,0x2fa43067,0xbb53bbc7,0xa94eaa7c,0x36c63843,0x2d4c2e78,0xb9bebaa3,
  0xa5e4a820,0x333d3526,0x29e32c1f,0xb6e3b8ab,0x9cb6a312,0x29b3304c,0x20b62711,0xadb0b438,
  0x3ba8bbf6,0xb4a52e46,0x3ba8bbf6,0x34a5ae46,0x3a2fbb0e,0xb913378b,0x3a2fbb0e,0x3913b78b,
  0x378bb913,0xbb0e3a2f,0x378bb913,0x3b0eba2f,0x2e46b4a5,0xbbf63ba8,0x2e46b4a5,0x3bf6bba8,
  0xb9133ba8,0x3a2fb4a5,0xb9133ba8,0xba2f34a5,0x378b2e46,0x3b0ebbf6,0x378b2e46,0xbb0e3bf6,
  0x3bf6bb0e,0xae46b78b,0x3bf6bb0e,0x2e46378b,0x34a5ba2f,0xbba83913,0x34a5ba2f,0x3ba8b913,
  0x2e46bb0e,0xbbf6378b,0x2e46bb0e,0x3bf6b78b,0xbba83a2f,0x34a53913,0xbba83a2f,0xb4a5b913,
  0x391334a5,0x3a2fbba8,0x391334a5,0xba2f3ba8,0x378bbbf6,0xbb0e2e46,0x378bbbf6,0x3b0eae46,
  0x378b3a2f,0x3b0eb913,0x378b3a2f,0xbb0e3913,0xae46bba8,0xbbf634a5,0xae46bba8,0x3bf6b4a5,
  0xb4a53bf6,0x3ba82e46,0xb4a53bf6,0xbba8ae46,0x3913bb0e,0xba2fb78b,0x3913bb0e,0x3a2f378b,
  0xbb0eb913,0xb78b3a2f,0xbb0eb913,0x378bba2f,0x3bf634a5,0x2e46bba8,0x3bf634a5,0xae463ba8,
  0xbba82e46,0x34a53bf6,0xbba82e46,0xb4a5bbf6,0x3a2fb78b,0xb913bb0e,0x3a2fb78b,0x39133b0e,
  0x3bf6378b,0xae46bb0e,0x3bf6378b,0x2e463b0e,0xb4a53913,0x3ba83a2f,0xb4a53913,0xbba8ba2f,
  0xba2fbba8,0xb91334a5,0xba2fbba8,0x3913b4a5,0x3b0e2e46,0xb78bbbf6,0x3b0e2e46,0x378b3bf6,
  0xba2fb4a5,0x39133ba8,0xba2fb4a5,0xb913bba8,0xbb0ebbf6,0xb78b2e46,0xbb0ebbf6,0x378bae46,
  0x2e46b78b,0xbbf6bb0e,0x2e46b78b,0x3bf63b0e,0x3ba83913,0xb4a5ba2f,0x3ba83913,0x34a53a2f,
  0x34a52e46,0xbba8bbf6,0x34a52e46,0x3ba83bf6,0x3913378b,0xba2fbb0e,0x3913378b,0x3a2f3b0e,
  0x3b0e3a2f,0xb78bb913,0x3b0e3a2f,0x378b3913,0x3bf63ba8,0xae46b4a5,0x3bf63ba8,0x2e4634a5,
  0x34a5ae46,0x3ba8bbf6,0xb4a52e46,0x3ba8bbf6,0x3913b78b,0x3a2fbb0e,0xb913378b,0x3a2fbb0e,
  0x3b0eba2f,0x378bb913,0xbb0e3a2f,0x378bb913,0x3bf6bba8,0x2e46b4a5,0xbbf63ba8,0x2e46b4a5,
  0xba2f34a5,0xb9133ba8,0x3a2fb4a5,0xb9133ba8,0xbb0e3bf6,0x378b2e46,0x3b0ebbf6,0x378b2e46,
  0x2e46378b,0x3bf6bb0e,0xae46b78b,0x3bf6bb0e,0x3ba8b913,0x34a5ba2f,0xbba83913,0x34a5ba2f,
  0x3bf6b78b,0x2e46bb0e,0xbbf6378b,0x2e46bb0e,0xb4a5b913,0xbba83a2f,0x34a53913,0xbba83a2f,
  0xba2f3ba8,0x391334a5,0x3a2fbba8,0x391334a5,0x3b0eae46,0x378bbbf6,0xbb0e2e46,0x378bbbf6,
  0xbb0e3913,0x378b3a2f,0x3b0eb913,0x378b3a2f,0x3bf6b4a5,0xae46bba8,0xbbf634a5,0xae46bba8,
  0xbba8ae46,0xb4a53bf6,0x3ba82e46,0xb4a53bf6,0x3a2f378b,0x3913bb0e,0xba2fb78b,0x3913bb0e,
  0x378bba2f,0xbb0eb913,0xb78b3a2f,0xbb0eb913,0xae463ba8,0x3bf634a5,0x2e46bba8,0x3bf634a5,
  0xb4a5bbf6,0xbba82e46,0x34a53bf6,0xbba82e46,0x39133b0e,0x3a2fb78b,0xb913bb0e,0x3a2fb78b,
  0x2e463b0e,0x3bf6378b,0xae46bb0e,0x3bf6378b,0xbba8ba2f,0xb4a53913,0x3ba83a2f,0xb4a53913,
  0x3913b4a5,0xba2fbba8,0xb91334a5,0xba2fbba8,0x378b3bf6,0x3b0e2e46,0xb78bbbf6,0x3b0e2e46,
  0xb913bba8,0xba2fb4a5,0x39133ba8,0xba2fb4a5,0x378bae46,0xbb0ebbf6,0xb78b2e46,0xbb0ebbf6,
  0x3bf63b0e,0x2e46b78b,0xbbf6bb0e,0x2e46b78b,0x34a53a2f,0x3ba83913,0xb4a5ba2f,0x3ba83913,
  0x3ba83bf6,0x34a52e46,0xbba8bbf6,0x34a52e46,0x3a2f3b0e,0x3913378b,0xba2fbb0e,0x3913378b,
  0x378b3913,0x3b0e3a2f,0xb78bb913,0x3b0e3a2f,0x2e4634a5,0x3bf63ba8,0xae46b4a5,0x3bf63ba8,
  0x3aa73bd9,0x3c003c00,0x3872323e,0x80008000,0x323e3872,0x3c003c00,0x3bd93aa7,0x80008000,
  0xb872b23e,0x3c003c00,0x3aa73bd9,0x80008000,0xbbd9baa7,0x3c003c00,0x323e3872,0x80008000,
  0xb61fbb64,0xbaa7bbd9,0xbb64b61f,0x3872323e,0x3b64361f,0xb23eb872,0xb61fbb64,0x3bd93aa7,
  0x361f3b64,0x3872323e,0x3b64361f,0x3aa73bd9,0xbb64b61f,0x3bd93aa7,0x361f3b64,0x323e3872,
  0xb23e3aa7,0x361f3b64,0x3bd93872,0xbb64b61f,0xb872bbd9,0xbb64b61f,0xbaa7323e,0xb61fbb64,
  0x3bd93872,0xb61fbb64,0x323ebaa7,0x3b64361f,0xbaa7323e,0x3b64361f,0x38723bd9,0x361f3b64,
  0x39a8b9a8,0x323ebaa7,0xb9a8b9a8,0x3bd93872,0xb9a839a8,0x38723bd9,0x39a839a8,0xbaa7323e,
  0x39a8b9a8,0xbbd9b872,0xb9a8b9a8,0x323ebaa7,0xb9a839a8,0x3aa7b23e,0x39a839a8,0x38723bd9,
  0xbbd93872,0xb9a839a8,0x323e3aa7,0xb9a8b9a8,0x3aa7323e,0x39a8b9a8,0x3872bbd9,0x39a839a8,
  0xb23ebaa7,0xb9a839a8,0xbbd93872,0xb9a8b9a8,0xb8723bd9,0x39a8b9a8,0x3aa7323e,0x39a839a8,
  0x3b64b61f,0x3bd9b872,0x361fbb64,0x323e3aa7,0x361fbb64,0xbaa7b23e,0xbb64361f,0x3872bbd9,
  0xbb64361f,0x323e3aa7,0xb61f3b64,0xbbd93872,0xb61f3b64,0x3872bbd9,0x3b64b61f,0x3aa7323e,
  0xb872323e,0xbb64361f,0xbaa73bd9,0x361fbb64,0xbbd93aa7,0xb61f3b64,0xb23e3872,0xbb64361f,
  0xbaa73bd9,0x3b64b61f,0x3872b23e,0xb61f3b64,0xb23e3872,0x361fbb64,0x3bd9baa7,0x3b64b61f,
  0x80008000,0x3872b23e,0x3c00bc00,0xbaa73bd9,0x00008000,0x3bd9baa7,0x3c00bc00,0xb23e3872,
  0x00008000,0x3aa7bbd9,0x3c00bc00,0x3872b23e,0x00008000,0x323eb872,0x3c00bc00,0x3bd9baa7,
  0x3aa73bd9,0x3c003c00,0xb872b23e,0x00000000,0x323e3872,0x3c003c00,0xbbd9baa7,0x00000000,
  0xb872b23e,0x3c003c00,0xbaa7bbd9,0x00000000,0xbbd9baa7,0x3c003c00,0xb23eb872,0x00000000,
  0xb61fbb64,0xbaa7bbd9,0x3b64361f,0xb872b23e,0x3b64361f,0xb23eb872,0x361f3b64,0xbbd9baa7,
  0x361f3b64,0x3872323e,0xbb64b61f,0xbaa7bbd9,0xbb64b61f,0x3bd93aa7,0xb61fbb64,0xb23eb872,
  0xb23e3aa7,0x361f3b64,0xbbd9b872,0x3b64361f,0xb872bbd9,0xbb64b61f,0x3aa7b23e,0x361f3b64,
  0x3bd93872,0xb61fbb64,0xb23e3aa7,0xbb64b61f,0xbaa7323e,0x3b64361f,0xb872bbd9,0xb61fbb64,
  0x39a8b9a8,0x323ebaa7,0x39a839a8,0xbbd9b872,0xb9a839a8,0x38723bd9,0xb9a8b9a8,0x3aa7b23e,
  0x39a8b9a8,0xbbd9b872,0x39a839a8,0xb23e3aa7,0xb9a839a8,0x3aa7b23e,0xb9a8b9a8,0xb872bbd9,
  0xbbd93872,0xb9a839a8,0xb23ebaa7,0x39a839a8,0x3aa7323e,0x39a8b9a8,0xb8723bd9,0xb9a8b9a8,
  0xb23ebaa7,0xb9a839a8,0x3bd9b872,0x39a839a8,0xb8723bd9,0x39a8b9a8,0xbaa7b23e,0xb9a8b9a8,
  0x3b64b61f,0x3bd9b872,0xb61f3b64,0xb23ebaa7,0x361fbb64,0xbaa7b23e,0x3b64b61f,0xb8723bd9,
  0xbb64361f,0x323e3aa7,0x361fbb64,0x3bd9b872,0xb61f3b64,0x3872bbd9,0xbb64361f,0xbaa7b23e,
  0xb872323e,0xbb64361f,0x3aa7bbd9,0xb61f3b64,0xbbd93aa7,0xb61f3b64,0x323eb872,0x3b64b61f,
  0xbaa73bd9,0x3b64b61f,0xb872323e,0x361fbb64,0xb23e3872,0x361fbb64,0xbbd93aa7,0xbb64361f,
  0x80008000,0x3872b23e,0xbc003c00,0x3aa7bbd9,0x00008000,0x3bd9baa7,0xbc003c00,0x323eb872,
  0x00008000,0x3aa7bbd9,0xbc003c00,0xb872323e,0x00008000,0x323eb872,0xbc003c00,0xbbd93aa7,
  0x39ba3aec,0xaf65a5e4,0xbb93bbeb,0x334c29e3,0x377a38ae,0xb4efb2b9,0xba23baf9,0x38813670,
  0x342335c1,0xb833b699,0xb7c2b918,0x3a9539a4,0x2c6d3133,0xba4db930,0xb067b511,0x3bc73b4e,
  0x38c739b1,0xae67a51b,0xbb0bbb8f,0x3257291b,0x365f37e7,0xb43eb1ce,0xb980ba5a,0x37ee359f,
  0x332234ef,0xb71fb5a4,0xb6ccb881,0x39f23905,0x2bab307f,0xb939b85b,0xafa4b469,0x3b533ab8,
  0x37d7389d,0xad6aa452,0xba52baed,0x31602852,0x3550368b,0xb322b0e6,0xb8c9b99b,0x36cc34c9,
  0x32023423,0xb5ebb4b8,0xb5ceb7c2,0x39353858,0x2a7c2f98,0xb843b72e,0xae78b37d,0x3aa339fa,
  0x3642374d,0xac6da312,0xb96dba0b,0x30672711,0x344c3542,0xb1ceaffe,0xb802b8bf,0x359f33df,
  0x30e632b9,0xb4c6b3a7,0xb4c9b670,0x3862373d,0x294e2e34,0xb6c6b5c1,0xad4cb226,0x39be3918,
  0x34c63588,0xaae1a17f,0xb862b8f1,0x2edc257f,0x329f3409,0xb07fae34,0xb659b796,0x34693226,
  0x2f983133,0xb357b1e8,0xb37db511,0x36f935b6,0x28202cd2,0xb526b467,0xac1fb0cb,0x38ab3817,
  0x32b933c1,0xa8e99fdb,0xb670b753,0x2ce723db,0x30b231b4,0xae67ac6d,0xb499b587,0x32573067,
  0x2d6a2f65,0xb133b032,0xb160b34c,0x35113420,0x25e42ae1,0xb33db236,0xa9e3aedc,0x36e335fd,
  0x2ffe3099,0xa5e49cb6,0xb3dfb481,0x29e320b6,0x2d9c2ecd,0xababa94e,0xb191b2b9,0x2fa42d4c,
  0x2a7c2c6d,0xae34ad04,0xae78b067,0x322630fd,0x23122820,0xb04caf65,0xa711ac1f,0x3438334c,
  0x294e2a17,0x9fdb9648,0xad4cae14,0x23db1a48,0x27772885,0xa51ba312,0xab75ac83,0x291b2711,
  0x245225e4,0xa820a6ad,0xa852a9e3,0x2c1f2aac,0x1cb6217f,0xa9b3a8e9,0xa0b6a57f,0x2db02ce7,
  0x35293099,0x3bca3bfe,0x3bbb3558,0x359f3bc4,0x392237d8,0x3a9c3b53,0xaedc3a13,0xbc00b896,
  0x3aff3a2b,0x388c39ad,0xbb1dbb0b,0x35e5b877,0x3bed3b97,0x337d3687,0x39fab004,0x39e13bcd,
  0x39d833ae,0xba02bbeb,0x3bca36cc,0x3036bb8a,0x3b5d3be1,0x34c9b451,0xbbdca57f,0x34813bfa,
  0x23db3877,0x3bf33a2b,0x3a95b62b,0xb92bbb0b,0xbb43b842,0x380d3b28,0xb82d39d0,0x3b3338e7,
  0x3a023817,0xb8ab3b3e,0xb036395b,0xbbff3a71,0xb76aba4b,0x3ab1b989,0x3b05b73d,0xb6423abf,
  0x2f403ba6,0xbbd2362b,0x3a1bbbf6,0x39beb257,0x3408bbfb,0x3be7a711,0xb540b438,0x3b43bbe3,
  0x359f38bf,0x3b2ebae0,0xb8ab39e9,0x3aedb9f2,0x39b5bbd0,0xba23afa4,0xb2883670,0x3bf4bb9b,
  0xbb703257,0xb4693ba6,0x32b99a48,0x3b9ebbf6,0x291b3a87,0x3bedb93e,0x38b5b687,0x39fabaf3,
  0xbb2e3a69,0xb8383964,0xbaed3b39,0x369e3822,0xbbf83bb4,0xb1f435ce,0x3a3b2ce7,0x399bbbe1,
  0xbbb13bf7,0x31c31a48,0x34e1bbaa,0xbb583226,0xba623b28,0x382db5b6,0xbbfd38e7,0xa91b3ac6,
  0xbbff3ad9,0x2c1fb8c9,0xb8383b86,0xba5ab6e3,0xb5fd3a8e,0xbb1737d8,0x3a9cb9c7,0x37ac3a13,
  0x3992b226,0xba433bf7,0xbbdf3614,0xad4cbbaa,0x3b82bbcd,0x34083511,0x3bc72711,0xb5403bf0,
  0xac1f3bc1,0x3be53570,0x3a5a3bfd,0x397630cb,0xb4c9bbf1,0xbbd5257f,0xb48134f9,0x3b6b3bd0,
  0x38fb3b11,0x3ab8b614,0xbbf9ba33,0xa3db386d,0xbae6b93e,0xb8b53980,0xb6f9baf3,0xbb82b8a0,
  0x369e3be9,0xbb93b3df,0x3be53bfe,0xb420aaac,0xbc00b84d,0x2db0ba4b,0x3ab13b74,0xb905b73d,
  0x3659b86d,0x3aff3b11,0x385839a4,0xbb1dba33,0x396d3be3,0xba622c83,0x30fd35b6,0xbbfdbbb7,
  0xbb93bbeb,0x334c29e3,0xb420bb8a,0x3b7d33ae,0xba23baf9,0x38813670,0x3bf43935,0xa0b63a8e,
  0xb7c2b918,0x3a9539a4,0xb7533796,0xbb70baa3,0xb067b511,0x3bc73b4e,0xb951bbf0,0x396db31b,
  0xb976bbc4,0xb948b099,0x334cbb3e,0xbbeeb558,0x3642b191,0xbba2bbb4,0x31f43c00,0x3badace7,
  0x3c003aa3,0xaf40b918,0xb88cbb62,0xba1b3796,0x36b53ac6,0x3ae63726,0x3ad33980,0x36f9ba52,
  0x3948bae0,0x3a7f36cc,0x3beeb9f2,0xa85238bf,0xbb1738f1,0xb862b9c7,0x37acbb22,0x3b5db84d,
  0x3bf3b4b1,0x32b93b62,0xb92b2e78,0x3992bbd7,0xbbbeac83,0x30fdbbff,0xbb8f3bb7,0xb6b5b160,
  0x3b7dba71,0xb710b817,0x3a7fb964,0x3802b95b,0xb99bb2ea,0xb9223bf1,0x3bd5bb53,0x2edcb4f9,
  0xb5e53bd7,0x3bb1b4b1,0x3bd2bc00,0xb4e12e78,0x3bfeb8a0,0xb067ba0b,0x3a78bb4e,0xb95137ee,
  0x3710b8c9,0xbacc39e9,0xb802b6e3,0xbb493ad9,0x2db0b451,0xbbdc3b74,0xb9053bfa,0x39b53191,
  0xb4692e14,0xbbdf3c00,0x3b9eb499,0x3659bbda,0xb8d33726,0xbad33b79,0xab75ba52,0xbbfe3842,
  0xa852b822,0x3bfcba69,0xbaccb570,0x38ddbb39,0xbb6b3896,0x376abaf9,0x38813989,0xbb053935,
  0xb9be3bda,0xb8fb2e14,0xb1c3bb67,0x3bf9b499,0x3587331b,0xbbbe3b97,0xb37d3bff,0xbb8fb004,
  0xbbfcb3df,0xb12e3b86,0xb8ddaaac,0x39d83be9,0x3ba2afa4,0xb288bc00,0xbbadbb9b,0xb5fd32ea,
  0xba433780,0x38583b67,0xad4cb90e,0xbc00baaa,0x380dba0b,0xba78b9d0,0x3b3337ee,0xb587ba87,
  0xbb49b0cb,0xb529bbc1,0xb12e29e3,0xbbbbbbfd,0xa0b6babf,0x3bf838f1,0xb862b5ce,0xba3bbb22,
  0x3b583aaa,0xb7c23780,0xbab8b9ad,0xb753b90e,0xb9e13160,0xb8d3bbfb,0xbbe7bb79,0xab75b438,
};

enum : uint32_t {
    OFF_C = 0,
    OFF_BAR = 5120,
    OFF_X = 6144,
    OFF_H = 55296,
    OFF_K = 104448, KP = 6912,
    OFF_V = 159744, VP = 6528,
    OFF_TAB = 88064, TABP = 10912,
    OFF_U = 175360, UP = 4352,
    OFF_PT = 211968,
    OFF_F1 = 215040,
    SMEM_BYTES = 227328,
    BAR_K = 0, BAR_X = 8, BAR_Y = 16, BAR_PD = 24, BAR_ED = 32, BAR_H = 40, BAR_H2 = 52
};
#define NB_CLUSTERS 12
#define NA_CLUSTERS 18

struct __align__(64) Maps { CUtensorMap k, kh, v, q32, q16, o32, o16, u; };
struct Ptrs {
    const uint16_t *are, *aim, *bre, *bim, *cre, *cim, *logdt, *dskip, *shiftk, *ssmk, *ssmd;
    uint16_t* out;
    const uint32_t* frag;
};

#define M2MASK 0
#define M4MASK 0
extern __shared__ __align__(1024) unsigned char smem[];
#define C0_ 0
#define MK2(i) do { if (M2MASK && threadIdx.x == 384) { unsigned c_; asm volatile("mov.u32 %0, %%clock;" : "=r"(c_)::"memory"); *(volatile unsigned*)(smem + 5632 + (i) * 4) = c_ - C0_; } } while (0)
#define MK4(i) do { if (((M4MASK >> ((i) - 19)) & 1) && threadIdx.x == 32 * MKW) { unsigned c_; asm volatile("mov.u32 %0, %%clock;" : "=r"(c_)::"memory"); *(volatile unsigned*)(smem + 5632 + (i) * 4) = c_; } } while (0)
#define MARK(i)
#define MARK_BEGIN()
#define MARK_END()
#define TRACE_BYTES 0

#define NCTA (4 * (NA_CLUSTERS + NB_CLUSTERS))
#define OUT_STG 1
#define BDELAY 400
#define ADELAY 2800
#define PROMO CU_TENSOR_MAP_L2_PROMOTION_NONE
#define GAP01 800
#define GOPOS 2
#define QLAG 1
#define LAA 2
#define MKW 1
#define LA 2
#define NH0 2
#define DI __device__ __forceinline__
DI uint32_t mapa(uint32_t a, uint32_t r) { uint32_t d; asm("mapa.shared::cluster.u32 %0,%1,%2;" : "=r"(d) : "r"(a), "r"(r)); return d; }
DI void bar_wait(uint32_t bar) {
    uint32_t ok, it = 0;
    do {
        asm volatile("{.reg .pred p; mbarrier.try_wait.parity.shared::cta.b64 p,[%1],0; selp.u32 %0,1,0,p;}" : "=r"(ok) : "r"(bar) : "memory");
        if (++it > (1u << 24)) __trap();
    } while (!ok);
}
DI bool bar_test(uint32_t bar) {
    uint32_t ok;
    asm volatile("{.reg .pred p; mbarrier.test_wait.parity.shared::cta.b64 p,[%1],0; selp.u32 %0,1,0,p;}" : "=r"(ok) : "r"(bar) : "memory");
    return __ballot_sync(0xffffffffu, ok) == 0xffffffffu;
}
DI bool elect() {
    uint32_t p;
    asm volatile("{.reg .pred q; elect.sync _|q,0xffffffff; selp.u32 %0,1,0,q;}" : "=r"(p));
    return p;
}
DI void bar_init(uint32_t bar, uint32_t cnt) { asm volatile("mbarrier.init.shared::cta.b64 [%0],%1;" ::"r"(bar), "r"(cnt) : "memory"); }
DI void bar_expect(uint32_t bar, uint32_t bytes) { asm volatile("mbarrier.arrive.expect_tx.shared::cta.b64 _,[%0],%1;" ::"r"(bar), "r"(bytes) : "memory"); }
DI void init_fence() { asm volatile("fence.mbarrier_init.release.cluster;" ::: "memory"); asm volatile("fence.proxy.async.shared::cta;" ::: "memory"); }
DI bool bar_test1(uint32_t bar) {
    uint32_t ok;
    asm volatile("{.reg .pred p; mbarrier.test_wait.parity.shared::cta.b64 p,[%1],0; selp.u32 %0,1,0,p;}" : "=r"(ok) : "r"(bar) : "memory");
    return ok;
}
DI void bar_arrive(uint32_t bar) { asm volatile("mbarrier.arrive.shared::cta.b64 _,[%0];" ::"r"(bar) : "memory"); }
DI void st_async(uint32_t a, uint32_t bar, uint32_t x, uint32_t y, uint32_t z, uint32_t w) {
    asm volatile("st.async.weak.shared::cluster.mbarrier::complete_tx::bytes.v4.b32 [%0],{%2,%3,%4,%5},[%1];" ::"r"(a), "r"(bar), "r"(x), "r"(y), "r"(z), "r"(w) : "memory");
}
DI void st_async_p(bool p, uint32_t a, uint32_t bar, uint32_t x, uint32_t y, uint32_t z, uint32_t w) {
    asm volatile("{.reg .pred q; setp.ne.u32 q,%6,0; @q st.async.weak.shared::cluster.mbarrier::complete_tx::bytes.v4.b32 [%0],{%2,%3,%4,%5},[%1];}" ::"r"(a), "r"(bar), "r"(x), "r"(y), "r"(z), "r"(w), "r"((uint32_t)p) : "memory");
}
DI void bulk_g2s(uint32_t dst, const void* src, uint32_t bytes, uint32_t bar) {
    asm volatile("cp.async.bulk.shared::cluster.global.mbarrier::complete_tx::bytes [%0],[%1],%2,[%3];" ::"r"(dst), "l"(src), "r"(bytes), "r"(bar) : "memory");
}
DI void tma3(uint32_t dst, const CUtensorMap* m, int c0, int c1, int c2, uint32_t bar) {
    asm volatile("cp.async.bulk.tensor.3d.shared::cluster.global.mbarrier::complete_tx::bytes [%0],[%1,{%3,%4,%5}],[%2];" ::"r"(dst), "l"(m), "r"(bar), "r"(c0), "r"(c1), "r"(c2) : "memory");
}
DI void tma2(uint32_t dst, const CUtensorMap* m, int c0, int c1, uint32_t bar) {
    asm volatile("cp.async.bulk.tensor.2d.shared::cluster.global.mbarrier::complete_tx::bytes [%0],[%1,{%3,%4}],[%2];" ::"r"(dst), "l"(m), "r"(bar), "r"(c0), "r"(c1) : "memory");
}
DI void tma2_st(const CUtensorMap* m, int c0, int c1, uint32_t src) {
    asm volatile("cp.async.bulk.tensor.2d.global.shared::cta.bulk_group [%0,{%2,%3}],[%1];" ::"l"(m), "r"(src), "r"(c0), "r"(c1) : "memory");
}
DI void ldsm4t(uint32_t (&r)[4], uint32_t a) {
    asm volatile("ldmatrix.sync.aligned.m8n8.x4.trans.shared.b16 {%0,%1,%2,%3},[%4];" : "=r"(r[0]), "=r"(r[1]), "=r"(r[2]), "=r"(r[3]) : "r"(a) : "memory");
}
DI uint4 lds128(uint32_t a) { uint4 v; asm volatile("ld.shared.v4.u32 {%0,%1,%2,%3},[%4];" : "=r"(v.x), "=r"(v.y), "=r"(v.z), "=r"(v.w) : "r"(a) : "memory"); return v; }
DI uint2 lds64(uint32_t a) { uint2 v; asm volatile("ld.shared.v2.u32 {%0,%1},[%2];" : "=r"(v.x), "=r"(v.y) : "r"(a) : "memory"); return v; }
DI uint32_t lds32(uint32_t a) { uint32_t v; asm volatile("ld.shared.u32 %0,[%1];" : "=r"(v) : "r"(a) : "memory"); return v; }
DI uint32_t lds16(uint32_t a) { uint32_t v; asm volatile("ld.shared.u16 %0,[%1];" : "=r"(v) : "r"(a) : "memory"); return v; }
DI void sts128(uint32_t a, uint32_t x, uint32_t y, uint32_t z, uint32_t w) { asm volatile("st.shared.v4.u32 [%0],{%1,%2,%3,%4};" ::"r"(a), "r"(x), "r"(y), "r"(z), "r"(w) : "memory"); }
DI void sts64(uint32_t a, uint32_t x, uint32_t y) { asm volatile("st.shared.v2.u32 [%0],{%1,%2};" ::"r"(a), "r"(x), "r"(y) : "memory"); }
DI void sts32(uint32_t a, uint32_t x) { asm volatile("st.shared.u32 [%0],%1;" ::"r"(a), "r"(x) : "memory"); }
DI void sts16(uint32_t a, uint32_t x) { asm volatile("st.shared.u16 [%0],%1;" ::"r"(a), "r"(x) : "memory"); }
DI uint32_t hfma(uint32_t a, uint32_t b, uint32_t c) { uint32_t d; asm("fma.rn.f16x2 %0,%1,%2,%3;" : "=r"(d) : "r"(a), "r"(b), "r"(c)); return d; }
DI uint32_t hfms(uint32_t a, uint32_t b, uint32_t c) { uint32_t d; asm("{.reg .b32 t; neg.f16x2 t,%1; fma.rn.f16x2 %0,t,%2,%3;}" : "=r"(d) : "r"(a), "r"(b), "r"(c)); return d; }
DI uint32_t hmul(uint32_t a, uint32_t b) { uint32_t d; asm("mul.rn.f16x2 %0,%1,%2;" : "=r"(d) : "r"(a), "r"(b)); return d; }
DI uint32_t hadd(uint32_t a, uint32_t b) { uint32_t d; asm("add.rn.f16x2 %0,%1,%2;" : "=r"(d) : "r"(a), "r"(b)); return d; }
DI uint32_t hsub(uint32_t a, uint32_t b) { uint32_t d; asm("sub.rn.f16x2 %0,%1,%2;" : "=r"(d) : "r"(a), "r"(b)); return d; }
DI uint32_t bmul(uint32_t a, uint32_t b) { uint32_t d; asm("mul.rn.bf16x2 %0,%1,%2;" : "=r"(d) : "r"(a), "r"(b)); return d; }
DI uint32_t bfma(uint32_t a, uint32_t b, uint32_t c) { uint32_t d; asm("fma.rn.bf16x2 %0,%1,%2,%3;" : "=r"(d) : "r"(a), "r"(b), "r"(c)); return d; }
DI uint32_t bfms(uint32_t a, uint32_t b, uint32_t c) { uint32_t d; asm("{.reg .b32 t; neg.bf16x2 t,%3; fma.rn.bf16x2 %0,%1,%2,t;}" : "=r"(d) : "r"(a), "r"(b), "r"(c)); return d; }
DI uint32_t badd(uint32_t a, uint32_t b) { uint32_t d; asm("add.rn.bf16x2 %0,%1,%2;" : "=r"(d) : "r"(a), "r"(b)); return d; }
DI uint32_t bsub(uint32_t a, uint32_t b) { uint32_t d; asm("sub.rn.bf16x2 %0,%1,%2;" : "=r"(d) : "r"(a), "r"(b)); return d; }
DI uint32_t bmaxabs(uint32_t a, uint32_t b) { uint32_t d; asm("max.xorsign.abs.bf16x2 %0,%1,%2;" : "=r"(d) : "r"(a), "r"(b)); return d; }
DI uint32_t cvt_h2(float lo, float hi) { uint32_t d; asm("cvt.rn.f16x2.f32 %0,%1,%2;" : "=r"(d) : "f"(hi), "f"(lo)); return d; }
DI uint32_t cvt_b2(float lo, float hi) { uint32_t d; asm("cvt.rn.bf16x2.f32 %0,%1,%2;" : "=r"(d) : "f"(hi), "f"(lo)); return d; }
DI uint32_t h2_to_b2(uint32_t h) {
    float lo, hi;
    asm("{.reg .b16 l,h; mov.b32 {l,h},%2; cvt.f32.f16 %0,l; cvt.f32.f16 %1,h;}" : "=f"(lo), "=f"(hi) : "r"(h));
    return cvt_b2(lo, hi);
}
DI uint32_t prmt(uint32_t a, uint32_t b, uint32_t s) { uint32_t d; asm("prmt.b32 %0,%1,%2,%3;" : "=r"(d) : "r"(a), "r"(b), "r"(s)); return d; }
DI uint32_t ldg16(const uint16_t* p) { uint32_t v; asm volatile("ld.global.nc.u16 %0,[%1];" : "=r"(v) : "l"(p)); return v; }
DI uint4 ldg128(const void* p) { uint4 v; asm volatile("ld.global.nc.v4.u32 {%0,%1,%2,%3},[%4];" : "=r"(v.x), "=r"(v.y), "=r"(v.z), "=r"(v.w) : "l"(p)); return v; }
DI float blo(uint32_t v) { return __uint_as_float(v << 16); }
DI float bhi(uint32_t v) { return __uint_as_float(v & 0xffff0000u); }

DI void mma_bf(float (&c)[4], const uint32_t* a, uint32_t b0, uint32_t b1, float i0, float i2) {
    asm("mma.sync.aligned.m16n8k16.row.col.f32.bf16.bf16.f32 {%0,%1,%2,%3},{%4,%5,%6,%7},{%8,%9},{%10,%11,%12,%11};"
        : "=f"(c[0]), "=f"(c[1]), "=f"(c[2]), "=f"(c[3]) : "r"(a[0]), "r"(a[1]), "r"(a[2]), "r"(a[3]), "r"(b0), "r"(b1), "f"(i0), "f"(0.f), "f"(i2));
}
DI void mma_h_z(uint32_t& d0, uint32_t& d1, const uint32_t* a, uint32_t b0, uint32_t b1) {
    asm("mma.sync.aligned.m16n8k16.row.col.f16.f16.f16.f16 {%0,%1},{%2,%3,%4,%5},{%6,%7},{%8,%8};"
        : "=r"(d0), "=r"(d1) : "r"(a[0]), "r"(a[1]), "r"(a[2]), "r"(a[3]), "r"(b0), "r"(b1), "r"(0));
}
DI void mma_h(uint32_t& d0, uint32_t& d1, const uint32_t* a, uint32_t b0, uint32_t b1) {
    asm("mma.sync.aligned.m16n8k16.row.col.f16.f16.f16.f16 {%0,%1},{%2,%3,%4,%5},{%6,%7},{%0,%1};"
        : "+r"(d0), "+r"(d1) : "r"(a[0]), "r"(a[1]), "r"(a[2]), "r"(a[3]), "r"(b0), "r"(b1));
}
DI void mma_hf_z(float* c, const uint32_t* a, uint32_t b0, uint32_t b1) {
    asm("mma.sync.aligned.m16n8k16.row.col.f32.f16.f16.f32 {%0,%1,%2,%3},{%4,%5,%6,%7},{%8,%9},{%10,%10,%10,%10};"
        : "=f"(c[0]), "=f"(c[1]), "=f"(c[2]), "=f"(c[3]) : "r"(a[0]), "r"(a[1]), "r"(a[2]), "r"(a[3]), "r"(b0), "r"(b1), "f"(0.f));
}
DI void mma_hf(float* c, const uint32_t* a, uint32_t b0, uint32_t b1) {
    asm("mma.sync.aligned.m16n8k16.row.col.f32.f16.f16.f32 {%0,%1,%2,%3},{%4,%5,%6,%7},{%8,%9},{%0,%1,%2,%3};"
        : "+f"(c[0]), "+f"(c[1]), "+f"(c[2]), "+f"(c[3]) : "r"(a[0]), "r"(a[1]), "r"(a[2]), "r"(a[3]), "r"(b0), "r"(b1));
}
template <int N> DI void ldq(uint32_t (&r)[N], uint32_t addr) {
#pragma unroll
    for (int i = 0; i < N / 4; i++) { uint4 v = lds128(addr + i * 512); r[4 * i] = v.x; r[4 * i + 1] = v.y; r[4 * i + 2] = v.z; r[4 * i + 3] = v.w; }
}

DI void rotp(uint32_t& re, uint32_t& im, uint32_t t, uint32_t s) { re = hfma(t, im, re); im = hfma(s, re, im); re = hfma(t, im, re); }
DI void rotm(uint32_t& re, uint32_t& im, uint32_t t, uint32_t s) { re = hfms(t, im, re); im = hfms(s, re, im); re = hfms(t, im, re); }
template <bool SKIP, bool SCALE = false>
DI void fwd1(const uint32_t (&b)[4], const uint32_t (&F1)[8], const uint32_t (&tw)[4], uint32_t (&z)[8], float dsk = 0.f, uint32_t sc = 0) {
    uint32_t e0, e1, o0, o1;
    if (SCALE) {
        const uint32_t t0 = bmul(b[2], sc), t1 = bmul(b[3], sc);
        e0 = bfma(b[0], sc, t0); e1 = bfma(b[1], sc, t1); o0 = bfms(b[0], sc, t0); o1 = bfms(b[1], sc, t1);
    } else { e0 = badd(b[0], b[2]); e1 = badd(b[1], b[3]); o0 = bsub(b[0], b[2]); o1 = bsub(b[1], b[3]); }
#pragma unroll
    for (int mu = 0; mu < 2; mu++) {
        float ce[4], co[4];
        float i0 = SKIP ? blo(F1[4 * mu]) * dsk : 0.f, i2 = SKIP ? blo(F1[4 * mu + 1]) * dsk : 0.f;
        mma_bf(ce, &F1[4 * mu], e0, e1, i0, i2);
        mma_bf(co, &F1[4 * mu], o0, o1, i0, i2);
        uint32_t p = cvt_h2(ce[0], ce[1]), u = cvt_h2(ce[2], ce[3]), r = cvt_h2(co[0], co[1]), q = cvt_h2(co[2], co[3]);
        rotp(p, q, tw[mu], tw[2 + mu]);
        rotp(r, u, tw[mu], tw[2 + mu]);
        z[mu] = p; z[2 + mu] = q; z[4 + mu] = r; z[6 + mu] = u;
    }
}
DI void fwd2(const uint32_t (&z)[8], const uint32_t (&S)[8], uint32_t (&o)[8]) {
    mma_h_z(o[0], o[1], &z[0], S[0], S[1]); mma_h_z(o[2], o[3], &z[0], S[2], S[3]);
    mma_h_z(o[4], o[5], &z[4], S[4], S[5]); mma_h_z(o[6], o[7], &z[4], S[6], S[7]);
}
DI void inv1(const uint32_t (&d)[8], const uint32_t (&iA)[8], const uint32_t (&itw)[4], uint32_t (&z)[8]) {
#pragma unroll
    for (int h = 0; h < 2; h++) {
        mma_h_z(z[2 * h], z[2 * h + 1], &iA[0], hadd(d[h], d[2 + h]), hsub(d[4 + h], d[6 + h]));
        mma_h_z(z[4 + 2 * h], z[5 + 2 * h], &iA[4], hadd(d[4 + h], d[6 + h]), hsub(d[h], d[2 + h]));
        rotp(z[2 * h], z[4 + 2 * h], itw[h], itw[2 + h]);
        rotm(z[2 * h + 1], z[5 + 2 * h], itw[h], itw[2 + h]);
    }
}
template <bool FIRST>
DI void cmac(uint32_t (&d)[8], const uint32_t (&g)[8], const uint32_t (&x)[8]) {
#pragma unroll
    for (int i = 0; i < 4; i++) {
        d[i] = FIRST ? hmul(x[i], g[i]) : hfma(x[i], g[i], d[i]);
        d[4 + i] = FIRST ? hmul(x[i], g[4 + i]) : hfma(x[i], g[4 + i], d[4 + i]);
    }
#pragma unroll
    for (int i = 0; i < 4; i++) {
        d[i] = hfms(x[4 + i], g[4 + i], d[i]);
        d[4 + i] = hfma(x[4 + i], g[i], d[4 + i]);
    }
}
DI uint32_t warp_maxexp(uint32_t m) {
    m &= 0x7fff7fffu;
    m = max(m & 0xffffu, m >> 16);
    m = __reduce_max_sync(0xffffffffu, m) >> 7;
    return min(max(m, 66u), 188u);
}

template <int H> DI void send8(const uint32_t (&o)[8], uint32_t dst, uint32_t dst2, uint32_t bar) {
    const int a = H ? 7 : 0, d = H ? -1 : 1;
    uint32_t l[4], m[4];
#pragma unroll
    for (int i = 0; i < 4; i++) { l[i] = prmt(o[a + 2 * i * d], o[a + (2 * i + 1) * d], 0x5410); m[i] = prmt(o[a + 2 * i * d], o[a + (2 * i + 1) * d], 0x7632); }
    asm volatile("" : "+r"(m[0]), "+r"(m[1]), "+r"(m[2]), "+r"(m[3]));
    st_async(dst, bar, l[0], l[1], l[2], l[3]);
    st_async(dst2, bar, m[0], m[1], m[2], m[3]);
}

DI void h_fix(uint32_t (&b)[4]) {
    const bool up = threadIdx.x & 2;
    const uint32_t l0 = up ? b[2] : b[0], l1 = up ? b[3] : b[1], h0 = up ? b[0] : b[2], h1 = up ? b[1] : b[3];
    b[0] = l0; b[1] = l1;
    b[2] = __shfl_xor_sync(0xffffffffu, h0, 28); b[3] = __shfl_xor_sync(0xffffffffu, h1, 28);
}
DI void h_load(uint32_t (&b)[4], uint32_t addr) { ldsm4t(b, addr); h_fix(b); }
template <int MODE>
DI void h_block(const uint32_t (&b)[4], const uint32_t (&F1)[8], const uint32_t (&tw)[4], const uint32_t (&S)[8], uint32_t (&G)[8], uint32_t (&Hp)[8], float dsk, uint32_t sc) {
    uint32_t z[8], H[8];
    fwd1<MODE == 0, MODE == 2>(b, F1, tw, z, dsk, sc);
    fwd2(z, S, H);
#pragma unroll
    for (int i = 0; i < 4; i++) {
        G[i] = MODE ? hadd(H[i], Hp[4 + i]) : H[i];
        G[4 + i] = MODE ? hsub(H[4 + i], Hp[i]) : H[4 + i];
    }
#pragma unroll
    for (int i = 0; i < 8; i++) Hp[i] = H[i];
}
DI void g_spill(uint32_t a, const uint32_t (&o)[8]) { sts128(a, o[1], o[0], o[3], o[2]); sts128(a + 512, o[5], o[4], o[7], o[6]); }

DI void conv_channel(uint32_t sb, uint32_t w, bool isB, uint32_t xaddr, uint32_t xpitch, uint32_t ydst, uint32_t ybar, uint32_t ypitch, float dskip, int eadj,
                     uint32_t hmax, const uint16_t* hsrc, uint32_t dsk_raw) {
    const uint32_t lane = threadIdx.x & 31, hbase = sb + OFF_H + w * 4096, bars = sb + OFF_BAR;
    const uint32_t frag = sb + OFF_C + lane * 16, gsp = hbase + lane * 16, gs2 = isB ? gsp : sb + OFF_TAB + w * TABP + lane * 16, haddr = hbase + (lane & 15) * 32 + (((lane >> 4) ^ (lane >> 2)) & 1) * 16;
    const uint32_t f1p = frag + (OFF_F1 - OFF_C) + w * 1024;
    uint32_t F1[8], tw[4], S[8], G[4][8];
    uint32_t eh = 0;
    int seen = 0, first = 0;
    ldq(F1, frag); ldq(tw, frag + 2 * 512); ldq(S, frag + 3 * 512);
    if (hsrc) {
        bar_wait(bars + (BAR_H + w) * 8);
        if (elect()) bulk_g2s(hbase + 2048, hsrc + 1024, 2048, bars + (BAR_H2 + w) * 8);
        __syncwarp();
        dskip = blo(__shfl_sync(0xffffffffu, dsk_raw, w));
        MARK(1);
    }
    for (;;) {
        uint32_t Hp[8], hb[4][4];
        MK4(21);
        ldsm4t(hb[0], haddr);
        eh = warp_maxexp(bmaxabs(bmaxabs(bmaxabs(hb[0][0], hb[0][1]), bmaxabs(hb[0][2], hb[0][3])), bmaxabs(hmax, cvt_b2(dskip * 0.0625f, 0.f))));
        asm volatile("" : "+r"(eh)::"memory");
        h_fix(hb[0]);
#pragma unroll
        for (int d = 1; d < 4; d++) h_load(hb[d], haddr + d * 512);
#pragma unroll
        for (int i = 0; i < 8; i++) F1[i] = bmul(F1[i], (254u - eh) * 0x00800080u);
        h_block<0>(hb[0], F1, tw, S, G[0], Hp, (lane & 3) ? 0.f : dskip, 0);
#pragma unroll
        for (int d = 1; d < 4; d++) h_block<1>(hb[d], F1, tw, S, G[d], Hp, 0.f, 0);
        MARK(3); MK4(22);
        if (first == 0 && hsrc) bar_wait(bars + (BAR_H2 + w) * 8);
        uint32_t iA[8], itw[4], G1[8];
        {
            uint32_t T[8];
#pragma unroll
            for (int d = 0; d <= NH0; d++) h_load(hb[d], haddr + 2048 + d * 512);
            ldq(iA, frag + 5 * 512); ldq(itw, frag + 7 * 512); ldq(G1, frag + 8 * 512);
            h_block<1>(hb[0], F1, tw, S, T, Hp, 0.f, 0);
            g_spill(gs2, T);
            h_block<1>(hb[1], F1, tw, S, T, Hp, 0.f, 0);
            g_spill(gs2 + 1024, T);
        }
        MARK(17); MK4(23);
        if (first == 0) bar_wait(bars + BAR_X * 8);
        MARK(4); MK4(24);
        uint32_t oscale, hs;
        uint32_t X[4][8], D[5][8], Dn[8], Xr[2][8], o[4];
        uint32_t xa = xaddr, ya = ydst, yb = ybar;
        bool ready, bad = false;
        {
            uint32_t b[4], z[8], m = 0;
#pragma unroll 1
            for (int i = seen; i >= 0; i--) {
                ldsm4t(b, xaddr + i * xpitch);
                m = bmaxabs(bmaxabs(bmaxabs(b[0], b[1]), bmaxabs(b[2], b[3])), m);
            }
            ready = bar_test1(bars + (BAR_X + 1) * 8);
            const uint32_t ex = warp_maxexp(m);
            {
                uint32_t T[8];
                h_block<1>(hb[NH0], F1, tw, S, T, Hp, 0.f, 0);
                g_spill(gs2 + NH0 * 1024, T);
            }
            hs = (127u + ex - eh) * 0x00800080u;
            const uint32_t rs = (127u + eh - ex) * 0x00800080u;
#pragma unroll
            for (int i = 0; i < 8; i++) F1[i] = bmul(F1[i], rs);
            sts128(f1p, F1[0], F1[1], F1[2], F1[3]); sts128(f1p + 512, F1[4], F1[5], F1[6], F1[7]);
            oscale = (uint32_t)min(max((int)(ex + eh) - 127 + eadj, 1), 254) * 0x00800080u;
            fwd1<false>(b, F1, tw, z);
            fwd2(z, S, X[0]);
            cmac<true>(D[0], G[0], X[0]);
        }
#pragma unroll
        for (int j = 0; j <= 8; j++) {
            if (bad || !ready) {
                if (bad) { seen = j - 1; first = j - 1; break; }
                bar_wait(bars + (BAR_X + (j < 7 ? j + 1 : 7)) * 8);
            }
            if (j > 0) {
                st_async_p(j > first, ya, yb, o[0], o[1], o[2], o[3]);
                ya += ypitch; yb += 8; asm volatile("" : "+r"(ya), "+r"(yb));
                MARK(4 + j);
            }
            if (j == 8) break;
            uint32_t(&dj)[8] = j < 4 ? D[0] : D[j - 3];
            uint32_t(&xj)[8] = j < 4 ? X[j] : Xr[j & 1];
            uint32_t(&xn)[8] = j + 1 < 4 ? X[j + 1] : Xr[(j + 1) & 1];
            uint32_t(&dn)[8] = j + 1 < 4 ? Dn : D[j + 1 - 3 < 5 ? j + 1 - 3 : 4];
            if (j == 3) {
                cmac<true>(D[1], G[2], X[2]); cmac<false>(D[1], G[3], X[1]);
                cmac<true>(D[2], G[3], X[2]);
#pragma unroll
                for (int dl = 4; dl < 8; dl++) {
                    uint32_t U[8];
                    ldq(U, gs2 + (dl - 4) * 1024);
                    const uint32_t T[8] = {U[1], U[0], U[3], U[2], U[5], U[4], U[7], U[6]};
#pragma unroll
                    for (int i = 7 - dl; i >= 0; i--) {
                        if (dl == 4 && i >= 2) cmac<true>(D[dl + i - 3], T, X[i]); else cmac<false>(D[dl + i - 3], T, X[i]);
                    }
                }
                ldq(F1, f1p); ldq(iA, frag + 5 * 512); ldq(G1, frag + 8 * 512);
                ldq(tw, frag + 2 * 512); ldq(S, frag + 3 * 512); ldq(itw, frag + 7 * 512);
            }
            uint32_t b[4], zf[8], zi[8]; float y[8];
            if (j < 7) { xa += xpitch; asm volatile("" : "+r"(xa)); ldsm4t(b, xa); }
            if (j + NH0 + 1 < 4) h_load(hb[j + NH0 + 1], haddr + 2048 + (j + NH0 + 1) * 512);
            if (j < 6) ready = bar_test1(bars + (BAR_X + j + 2) * 8); else ready = true;
            inv1(dj, iA, itw, zi);
            if (j < 7) fwd1<false>(b, F1, tw, zf);
            if (j < 3) { cmac<true>(dn, G[j + 1], X[0]); if (j == 2) cmac<false>(dn, G[2], X[1]); }
            else if (j < 7) { cmac<false>(dn, G[1], xj); if (j + 3 < 8) cmac<false>(D[j + 3 - 3], G[3], xj); }
            mma_hf_z(&y[0], &zi[0], G1[0], G1[1]); mma_hf_z(&y[4], &zi[0], G1[2], G1[3]);
            mma_hf(&y[0], &zi[4], G1[4], G1[5]); mma_hf(&y[4], &zi[4], G1[6], G1[7]);
            if (j < 7) fwd2(zf, S, xn);
            if (j >= 1 && j < 3) cmac<false>(dn, G[1], xj);
            if (j >= 3 && j + 2 < 8) cmac<false>(D[j + 2 - 3], G[2], xj);
            if (j + NH0 + 1 < 4) {
                uint32_t T[8];
                h_block<2>(hb[j + NH0 + 1], F1, tw, S, T, Hp, 0.f, hs);
                g_spill(gs2 + (j + NH0 + 1) * 1024, T);
            }
            o[0] = bmul(cvt_b2(y[0], y[2]), oscale); o[1] = bmul(cvt_b2(y[1], y[3]), oscale);
            o[2] = bmul(cvt_b2(y[4], y[6]), oscale); o[3] = bmul(cvt_b2(y[5], y[7]), oscale);
            if (j >= 1) bad = __any_sync(0xffffffffu, j > seen && !(fabsf(y[0] + y[2]) <= 3.0e38f));
            if (j < 7) {
                cmac<false>(dn, G[0], xn);
                if (j + 1 < 4) {
#pragma unroll
                    for (int i = 0; i < 8; i++) D[0][i] = Dn[i];
                }
            }
        }
        if (!bad) {
            break;
        }
        if (hsrc) {
            __syncwarp();
#pragma unroll 1
            for (int i = 0; i < 8; i++) {
                uint4 v = __ldg((const uint4*)hsrc + i * 32 + lane);
                sts128(gsp + i * 512, v.x, v.y, v.z, v.w);
                hmax = bmaxabs(bmaxabs(bmaxabs(v.x, v.y), bmaxabs(v.z, v.w)), hmax);
            }
            __syncwarp();
        }
        ldq(F1, frag);
    }
}

struct Cx { uint32_t r, i; };
DI Cx cmul(Cx a, Cx b) { Cx d; d.r = hfms(a.i, b.i, hmul(a.r, b.r)); d.i = hfma(a.i, b.r, hmul(a.r, b.i)); return d; }
DI Cx cmulc(Cx a, Cx b) { Cx d; d.r = hfma(a.i, b.i, hmul(a.r, b.r)); d.i = hfms(a.r, b.i, hmul(a.i, b.r)); return d; }
DI void cexpf_(float a2, float b, float l, float& re, float& im) {
    float m, t = b * l;
    asm("ex2.approx.ftz.f32 %0,%1;" : "=f"(m) : "f"(a2 * l));
    re = m * __cosf(t); im = m * __sinf(t);
}
DI void csq(float& re, float& im) { float r = re * re - im * im; im = 2.f * re * im; re = r; }

DI void powers(float a0, float b0, float a1, float b1, Cx (&E)[11]) {
#pragma unroll
    for (int k = 0; k < 3; k++) {
        float r0, i0, r1, i1;
        const float l = k == 0 ? 1.f : k == 1 ? 16.f : 256.f;
        cexpf_(a0, b0, l, r0, i0); cexpf_(a1, b1, l, r1, i1);
        E[4 * k].r = cvt_h2(r0, r1); E[4 * k].i = cvt_h2(i0, i1);
#pragma unroll
        for (int q = 1; q < 4; q++) if (4 * k + q < 11) {
            csq(r0, i0); csq(r1, i1);
            E[4 * k + q].r = cvt_h2(r0, r1); E[4 * k + q].i = cvt_h2(i0, i1);
        }
    }
}
struct Tabs { Cx w[16], x[8], y[8], z[5], e; };
DI void products(const Cx (&E)[11], Cx c, Tabs& T) {
    T.w[0].r = 0x3c003c00u; T.w[0].i = 0; T.w[1] = E[3]; T.w[2] = E[4]; T.w[4] = E[5]; T.w[8] = E[6]; T.e = E[7];
    T.w[3] = cmul(T.w[2], T.w[1]); T.w[5] = cmul(T.w[4], T.w[1]); T.w[6] = cmul(T.w[4], T.w[2]); T.w[7] = cmul(T.w[4], T.w[3]);
#pragma unroll
    for (int r = 1; r < 8; r++) T.w[8 + r] = cmul(T.w[r], E[6]);
    T.x[0] = c; T.x[1] = cmulc(c, E[0]); T.x[2] = cmulc(c, E[1]); T.x[3] = cmulc(T.x[1], E[1]);
#pragma unroll
    for (int r = 0; r < 4; r++) T.x[4 + r] = cmulc(T.x[r], E[2]);
#pragma unroll
    for (int r = 0; r < 4; r++) T.y[r] = cmulc(T.x[2 * r], E[8]);
    T.y[4] = cmulc(c, E[9]); T.y[5] = cmulc(T.x[4], E[9]); T.y[6] = cmulc(T.y[0], E[9]); T.y[7] = cmulc(T.y[2], E[9]);
    T.z[0] = cmulc(c, E[10]); T.z[1] = cmulc(T.y[0], E[10]); T.z[2] = cmulc(T.y[4], E[10]); T.z[3] = cmulc(T.y[6], E[10]); T.z[4] = cmulc(T.z[0], E[10]);
}
DI void put_tabs(unsigned char* tab, const Tabs& T) {
    const uint32_t lane = threadIdx.x & 31;
#pragma unroll
    for (int r = 0; r < 8; r++) {
        *(uint4*)(tab + r * 576 + lane * 16) = make_uint4(T.w[r].r, T.w[8 + r].r, T.w[r].i, T.w[8 + r].i);
        *(uint4*)(tab + 4608 + r * 576 + lane * 16) = make_uint4(T.x[r].r, T.x[r].i, T.y[r].r, T.y[r].i);
    }
#pragma unroll
    for (int r = 0; r < 5; r++) *(uint2*)(tab + 9216 + r * 288 + lane * 8) = make_uint2(T.z[r].r, T.z[r].i);
    *(uint2*)(tab + 10656 + lane * 8) = make_uint2(T.e.r, T.e.i);
}
DI void mode_sum(const unsigned char* tab, uint32_t (&acc)[2][3][2]) {
    const uint32_t lane = threadIdx.x & 31, g = lane >> 2, c = lane & 3;
    const unsigned char *rw = tab + g * 576 + c * 16, *rz = tab + 9216 + min(g, 4u) * 288 + c * 8, *re = tab + 10656 + c * 8;
#pragma unroll
    for (int k = 0; k < 8; k++) {
        const uint4 wq = *(const uint4*)(rw + k * 64), xq = *(const uint4*)(rw + 4608 + k * 64);
        const uint2 zq = *(const uint2*)(rz + k * 32), eq = *(const uint2*)(re + k * 32);
        uint32_t A0[4] = {wq.x, wq.y, wq.z, wq.w}, A1[4];
        const Cx e = {eq.x, eq.y}, u0 = cmul(Cx{wq.x, wq.z}, e), u1 = cmul(Cx{wq.y, wq.w}, e);
        A1[0] = u0.r; A1[1] = u1.r; A1[2] = u0.i; A1[3] = u1.i;
        mma_h(acc[0][0][0], acc[0][0][1], A0, xq.x, xq.y); mma_h(acc[0][1][0], acc[0][1][1], A0, xq.z, xq.w); mma_h(acc[0][2][0], acc[0][2][1], A0, zq.x, zq.y);
        mma_h(acc[1][0][0], acc[1][0][1], A1, xq.x, xq.y); mma_h(acc[1][1][0], acc[1][1][1], A1, xq.z, xq.w); mma_h(acc[1][2][0], acc[1][2][1], A1, zq.x, zq.y);
    }
}

DI uint32_t gen_kernel(unsigned char* tab, unsigned char* h, const uint2 (&pv)[6], float dt, float& dskip, int& eadj, uint32_t gobar) {
    const uint32_t lane = threadIdx.x & 31, g = lane >> 2, c = lane & 3;
    float a2[4], bb[4], cr[4], ci[4];
    uint32_t mx = __float_as_uint(fabsf(dskip) * 6.103515625e-05f);
#pragma unroll
    for (int m = 0; m < 4; m++) {
        float v[6];
#pragma unroll
        for (int t = 0; t < 6; t++) { uint32_t w = (m & 2) ? pv[t].y : pv[t].x; v[t] = (m & 1) ? bhi(w) : blo(w); }
        a2[m] = (dt * v[0]) * 1.4426950408889634f; bb[m] = dt * v[1];
        float br = dt * v[2], bi = dt * v[3];
        cr[m] = v[4] * br - v[5] * bi; ci[m] = v[4] * bi + v[5] * br;
        mx = max(mx, max(__float_as_uint(cr[m]) & 0x7fffffffu, __float_as_uint(ci[m]) & 0x7fffffffu));
    }
    const uint32_t ec = min(max(__reduce_max_sync(0xffffffffu, mx) >> 23, 20u), 234u);
    const float sc = __uint_as_float((254u - ec) << 23);
    eadj = (int)ec - 127;
    dskip *= sc;
    MARK(13); MK4(20);
    uint32_t acc[2][3][2];
#pragma unroll
    for (int i = 0; i < 12; i++) acc[i / 6][(i / 2) % 3][i & 1] = 0;
    Cx E0[11], E1[11], c0 = {cvt_h2(cr[0] * sc, cr[1] * sc), cvt_h2(ci[0] * -sc, ci[1] * -sc)}, c1 = {cvt_h2(cr[2] * sc, cr[3] * sc), cvt_h2(ci[2] * -sc, ci[3] * -sc)};
    Tabs T;
    powers(a2[0], bb[0], a2[1], bb[1], E0);
    powers(a2[2], bb[2], a2[3], bb[3], E1);
    MARK(18);
    products(E0, c0, T);
    put_tabs(tab, T);
    __syncwarp();
    MARK(14);
    mode_sum(tab, acc);
    products(E1, c1, T);
    __syncwarp();
    if (threadIdx.x == 0) bar_arrive(gobar);
    MARK(15);
    put_tabs(tab, T);
    __syncwarp();
    mode_sum(tab, acc);
    __syncwarp();
    MARK(16);
    uint32_t hmax = 0;
#pragma unroll
    for (int q = 0; q < 4; q++) {
        const uint32_t r = g + 8 * q, v = h2_to_b2(acc[q >> 1][2][q & 1]);
        *(uint32_t*)(h + r * 16 + c * 4) = h2_to_b2(acc[q >> 1][0][q & 1]);
        const uint32_t v1 = h2_to_b2(acc[q >> 1][1][q & 1]);
        hmax = bmaxabs(hmax, v1);
        *(uint32_t*)(tab + (c < 2 ? 8 * r + 4 * c : 256 + 128 * (c - 2) + 4 * r)) = v1;
        if (c < 2 || (q == 0 && lane == 2)) { hmax = bmaxabs(hmax, c < 2 ? v : v & 0xffffu); *(uint16_t*)(tab + 512 + 128 * c + 2 * r) = (uint16_t)v; }
        if (c < 2) *(uint16_t*)(tab + 576 + 128 * c + 2 * r) = (uint16_t)(v >> 16);
    }
    __syncwarp();
    const uint2 v1 = *(const uint2*)(tab + lane * 8);
    const uint32_t n1 = *(const uint16_t*)(tab + lane * 8 + 8);
    uint32_t v2[2], n2[2], v3[4], n3[4];
#pragma unroll
    for (int i = 0; i < 2; i++) { v2[i] = *(const uint32_t*)(tab + 256 + (i * 32 + lane) * 4); n2[i] = *(const uint16_t*)(tab + 260 + (i * 32 + lane) * 4); }
#pragma unroll
    for (int i = 0; i < 4; i++) { v3[i] = *(const uint16_t*)(tab + 512 + (i * 32 + lane) * 2); n3[i] = *(const uint16_t*)(tab + 514 + (i * 32 + lane) * 2); }
    *(uint4*)(h + 512 + lane * 16) = make_uint4(prmt(v1.x, 0, 0x1010), prmt(v1.x, v1.y, 0x5432), prmt(v1.y, 0, 0x1010), prmt(v1.y, n1, 0x5432));
#pragma unroll
    for (int i = 0; i < 2; i++) *(uint4*)(h + 1024 + (i * 32 + lane) * 16) = make_uint4(prmt(v2[i], 0, 0x1010), v2[i], prmt(v2[i], 0, 0x3232), prmt(n2[i], 0, 0x1010));
    const uint32_t sel = (lane & 1) ? 0x5454 : 0x5410;
#pragma unroll
    for (int i = 0; i < 4; i++) {
        const uint32_t vv = prmt(v3[i], 0, 0x1010);
        *(uint4*)(h + 2048 + (i * 32 + lane) * 16) = make_uint4(vv, vv, prmt(v3[i], n3[i], sel), prmt(n3[i], 0, 0x1010));
    }
    __syncwarp();
    return hmax;
}

DI void load_raw(const Maps& M, uint32_t sb, bool isB, int ch0, int rank, int s) {
    const int a0 = 16 * s + 4 * rank;
    const uint32_t bar = sb + OFF_BAR + (BAR_K + s) * 8;
    if (isB) {
        tma3(sb + OFF_K + s * KP, &M.kh, ch0, 13, a0 - 1, bar);
        tma3(sb + OFF_K + s * KP + 384, &M.k, ch0, 0, a0, bar);
        tma3(sb + OFF_V + s * VP, &M.v, ch0, 0, a0, bar);
    } else tma3(sb + OFF_U + s * UP, &M.u, ch0, 0, a0, bar);
}
DI void load_q(const Maps& M, uint32_t sb, int ch0, int rank, int s) {
    bar_wait(sb + OFF_BAR + (BAR_PD + s) * 8);
    if (elect()) {
        tma2(sb + OFF_V + s * VP, &M.q32, ch0, 256 * s + 64 * rank, sb + OFF_BAR + (BAR_Y + s) * 8);
        tma2(sb + OFF_V + s * VP + 4096, &M.q16, ch0 + 32, 256 * s + 64 * rank, sb + OFF_BAR + (BAR_Y + s) * 8);
    }
    __syncwarp();
}
__global__ void __cluster_dims__(4, 1, 1) __launch_bounds__(512, 1)
ssm_conv_kernel(const Ptrs P, const __grid_constant__ Maps M) {
    extern __shared__ __align__(1024) unsigned char smem[];
    const uint32_t sb = (uint32_t)__cvta_generic_to_shared(smem);
    const uint32_t w = __shfl_sync(0xffffffffu, threadIdx.x >> 5, 0), lane = threadIdx.x & 31;
    const uint32_t cid = (blockIdx.x >> 2) + (gridDim.x == 4 * NA_CLUSTERS ? NB_CLUSTERS : 0), rank = blockIdx.x & 3;
    const bool isB = cid < NB_CLUSTERS;
    const int ch0 = isB ? 48 * cid : 32 * (cid - NB_CLUSTERS);
    const uint32_t bars = sb + OFF_BAR, nch = isB ? 12 : 8;
    MARK_BEGIN();
    const bool active = w < nch;
    const int ch = ch0 + nch * rank + w;
    const uint32_t hbase = sb + OFF_H + w * 4096, q0 = isB ? w : 3 * (w - 8);
    uint2 pv[6];
    uint32_t dsk_raw = 0, dt_raw = 0;
    if (w < 12) {
        if (isB || !active) {
            const uint32_t* src = P.frag + min(q0, 9u) * 128 + lane * 4;
            uint4 v = ldg128(src);
            pv[0] = make_uint2(v.x, v.y); pv[1] = make_uint2(v.z, v.w);
            if (isB) {
                dsk_raw = ldg16(P.ssmd + (ch - w) + min(lane, 11u));
                if (elect()) {
                    bar_init(bars + (BAR_H + w) * 8, 1); bar_init(bars + (BAR_H2 + w) * 8, 1);
                    bar_expect(bars + (BAR_H + w) * 8, 2048);
                    asm volatile("fence.mbarrier_init.release.cluster;" ::: "memory");
                    bulk_g2s(hbase, P.ssmk + (size_t)ch * 2048, 2048, bars + (BAR_H + w) * 8);
                    bar_expect(bars + (BAR_H2 + w) * 8, 2048);
                }
                __syncwarp();
            } else if (w < 11) {
                v = ldg128(src + 128); pv[2] = make_uint2(v.x, v.y); pv[3] = make_uint2(v.z, v.w);
                v = ldg128(src + 256); pv[4] = make_uint2(v.x, v.y); pv[5] = make_uint2(v.z, v.w);
            }
        } else {
            const size_t o = (size_t)ch * 128 + lane * 4;
            pv[0] = __ldg((const uint2*)(P.are + o)); pv[1] = __ldg((const uint2*)(P.aim + o)); pv[2] = __ldg((const uint2*)(P.bre + o));
            pv[3] = __ldg((const uint2*)(P.bim + o)); pv[4] = __ldg((const uint2*)(P.cre + o)); pv[5] = __ldg((const uint2*)(P.cim + o));
            dt_raw = ldg16(P.logdt + (ch - w) + (lane & 7));
            dsk_raw = ldg16(P.dskip + (ch - w) + (lane & 7));
            if (w == 0) { if (elect()) { bar_init(bars + BAR_H * 8, 1); asm volatile("fence.mbarrier_init.release.cluster;" ::: "memory"); } __syncwarp(); }
        }
    }
    MARK(19);
    if (w < 12) {
        if (active) asm volatile("barrier.cluster.arrive.relaxed.aligned;" ::: "memory");
        if (isB ? w < 10 : w >= 8) {
            const uint32_t ca = sb + OFF_C + q0 * 512 + lane * 16;
            sts128(ca, pv[0].x, pv[0].y, pv[1].x, pv[1].y);
            if (!isB && w < 11) { sts128(ca + 512, pv[2].x, pv[2].y, pv[3].x, pv[3].y); sts128(ca + 1024, pv[4].x, pv[4].y, pv[5].x, pv[5].y); }
        }
        if (!active) {
            asm volatile("barrier.cluster.arrive.release.aligned;" ::: "memory");
            asm volatile("barrier.cluster.wait.aligned;" ::: "memory");
        }
        if (isB) asm volatile("bar.sync 1, 384;" ::: "memory");
        asm volatile("setmaxnreg.inc.sync.aligned.u32 152;");
        MK4(19);
        float dskip = 0.f;
        int eadj = 0;
        uint32_t hmax = 0;
        if (active) {
            if (!isB) {
                dskip = blo(__shfl_sync(0xffffffffu, dsk_raw, w));
                hmax = gen_kernel(smem + OFF_TAB + w * TABP, smem + OFF_H + w * 4096, pv, blo(cvt_b2(expf(blo(__shfl_sync(0xffffffffu, dt_raw, w))), 0.f)), dskip, eadj, bars + BAR_H * 8);
            }
            asm volatile("barrier.cluster.wait.aligned;" ::: "memory");
            MK4(25);
            if (!isB) MARK(1);
            const uint32_t g = lane >> 2, c = lane & 3, cl = nch * rank + w;
            const uint32_t f = cl < 32 ? 2 * (cl >> 3) + (cl & 1) : 4 * ((cl >> 3) & 1) + 2 * (cl & 1);
            const uint32_t yl = (isB ? OFF_K : OFF_U) + cl * 128 + (g ^ f) * 16;
            const uint32_t slot = ((w & 1) * (nch >> 1) + (w >> 1)) ^ (isB ? (lane >> 1) & 3 : lane & 7);
            conv_channel(sb, w, isB, sb + OFF_X + lane * nch * 16 + slot * 16, nch * 512, mapa(sb + yl, c), mapa(bars + BAR_Y * 8, c), isB ? KP : UP, dskip, eadj,
                         hmax, isB ? P.ssmk + (size_t)ch * 2048 : nullptr, dsk_raw);
        }
    } else {
        const uint32_t iw = w - 12;
        asm volatile("setmaxnreg.dec.sync.aligned.u32 56;");
        if (iw == 3 && elect()) {
            asm volatile("prefetch.tensormap [%0];" ::"l"(isB ? &M.k : &M.u) : "memory");
            if (isB) { asm volatile("prefetch.tensormap [%0];" ::"l"(&M.kh) : "memory"); asm volatile("prefetch.tensormap [%0];" ::"l"(&M.v) : "memory"); }
        }
        __syncwarp();
        {
            const uint32_t b0 = bars + iw * 64;
            if (elect()) {
#pragma unroll
                for (int i = 0; i < 8; i++) bar_init(b0 + i * 8, iw < 3 ? 1 : 3);
            }
            __syncwarp();
            if (iw < 3 && lane < 8) bar_expect(b0 + lane * 8, iw == 0 ? (isB ? KP + VP : UP) : iw == 1 ? nch * 512 : (isB ? 12288 : 4096));
            init_fence();
            __syncwarp();
        }
        asm volatile("barrier.cluster.arrive.relaxed.aligned;" ::: "memory");
        if (iw == 0 && isB) {
            { const uint32_t t0 = clock(); while ((uint32_t)clock() - t0 < BDELAY) ; }
            if (elect()) load_raw(M, sb, isB, ch0, rank, 0);
            __syncwarp();
            { const uint32_t t0 = clock(); while ((uint32_t)clock() - t0 < GAP01) ; }
            if (elect()) load_raw(M, sb, isB, ch0, rank, 1);
            __syncwarp();
        }
        if (isB) {
            if (iw) {
                const uint32_t n = 32 * (iw - 1) + lane, a = n / 24, p = n - 24 * a, dr = p / 6, pl = p - 6 * dr, ag = 4 * rank + a, sw = (ag >> 1) & 3;
                const uint4 t = __ldg((const uint4*)(P.shiftk + (size_t)(ch0 + 2 * p) * 4));
                const uint32_t pt = sb + OFF_PT + (iw - 1) * 1024 + lane * 16;
                sts128(pt, sb + OFF_K + 384 + a * 1632 + p * 4, mapa(sb + OFF_X + ag * 192 + (pl ^ sw) * 16, dr), mapa(sb + OFF_X + ag * 192 + ((pl + 6) ^ sw) * 16, dr),
                       mapa(bars + BAR_X * 8, dr));
                sts128(pt + 512, prmt(t.x, t.z, 0x5410), prmt(t.x, t.z, 0x7632), prmt(t.y, t.w, 0x5410), prmt(t.y, t.w, 0x7632));
            }
            asm volatile("bar.sync 2, 128;" ::: "memory");
            asm volatile("barrier.cluster.wait.aligned;" ::: "memory");
#pragma unroll 1
            for (uint32_t s = 0; s < 8; s++) {
                const uint32_t r = (iw - s - 1) & 3;
                if (r == 3) {
                    if (s + LA < 8) {
                        bar_wait(bars + (BAR_K + s) * 8);
                        if (elect()) { if (LA == 3 && s == 0) load_raw(M, sb, isB, ch0, rank, 2); load_raw(M, sb, isB, ch0, rank, s + LA); }
                        __syncwarp();
                    }
                    if (s >= QLAG) load_q(M, sb, ch0, rank, s - QLAG);
                } else {
                    const uint4 ad = lds128(sb + OFF_PT + r * 1024 + lane * 16), wt = lds128(sb + OFF_PT + r * 1024 + 512 + lane * 16);
                    const uint32_t ka = ad.x + s * KP, va = ad.x + (OFF_V - OFF_K - 384) + s * VP, dst = ad.y + s * 6144, dst2 = ad.z + s * 6144, bar = ad.w + s * 8;
                    bar_wait(bars + (BAR_K + s) * 8);
                    MK2(s);
                    uint32_t k[19], v[16];
                    k[0] = lds32(ka - 4 * 96); k[1] = lds32(ka - 3 * 96); k[2] = lds32(ka - 2 * 96);
#pragma unroll
                    for (int i = 0; i < 8; i++) { k[3 + i] = lds32(ka + i * 96); v[i] = lds32(va + i * 96); }
                    uint32_t o[8];
#pragma unroll
                    for (int i = 0; i < 8; i++) o[i] = bmul(bfma(k[i + 3], wt.x, bfma(k[i + 2], wt.y, bfma(k[i + 1], wt.z, bmul(k[i], wt.w)))), v[i]);
#pragma unroll
                    for (int i = 8; i < 16; i++) { k[3 + i] = lds32(ka + i * 96); v[i] = lds32(va + i * 96); }
                    __syncwarp();
                    if (lane == 0) bar_arrive(bars + (BAR_PD + s) * 8);
                    send8<0>(o, dst, dst2, bar);
#pragma unroll
                    for (int i = 8; i < 16; i++) o[i - 8] = bmul(bfma(k[i + 3], wt.x, bfma(k[i + 2], wt.y, bfma(k[i + 1], wt.z, bmul(k[i], wt.w)))), v[i]);
                    send8<1>(o, dst + 3072, dst2 + 3072, bar);
                }
            }
            if (iw == 3) { for (uint32_t s = 8 - QLAG; s < 8; s++) load_q(M, sb, ch0, rank, s); }
        } else if (iw == 0) {
            asm volatile("barrier.cluster.wait.aligned;" ::: "memory");
            bar_wait(bars + BAR_H * 8);
#pragma unroll 1
            for (uint32_t s = 0; s < 8; s++) {
                if (s >= LAA) bar_wait(bars + (BAR_K + s - LAA) * 8);
                if (elect()) load_raw(M, sb, isB, ch0, rank, s);
                __syncwarp();
            }
        } else {
            asm volatile("barrier.cluster.wait.aligned;" ::: "memory");
#pragma unroll 1
            for (uint32_t s = 0; s < 8; s++) {
                bar_wait(bars + (BAR_K + s) * 8);
                MARK(1 + s);
#pragma unroll 1
                for (uint32_t u = (iw + 2 + 2 * s) % 3; u < 4; u += 3) {
                    const uint32_t h = u & 1, a = (u & 2) + (lane >> 4), p = lane & 15, d = p >> 2, ga = 4 * rank + a;
                    const uint32_t ua = sb + OFF_U + s * UP + a * 1088 + p * 4 + h * 512;
                    const uint32_t dst = mapa(sb + OFF_X + s * 4096 + (16 * h + ga) * 128 + (((p & 3) ^ ga) & 7) * 16, d), bar = mapa(bars + (BAR_X + s) * 8, d);
                    uint32_t o[8];
#pragma unroll
                    for (int i = 0; i < 8; i++) o[i] = lds32(ua + i * 64);
                    if (h) send8<1>(o, dst, dst ^ 64, bar); else send8<0>(o, dst, dst ^ 64, bar);
                }
            }
        }
        MARK(9); MK2(8);
        const uint32_t g = lane >> 2, c = lane & 3, rr = lane & 7, ti = lane >> 3, G = 2 * iw;
        const uint32_t row0 = 16 * (g >> 1) + ((g & 1) ? 15 - G : G), row2 = 16 * (g >> 1) + ((g & 1) ? 15 - G - (c >> 1) : G + (c >> 1));
        const int rd = (g & 1) ? -1 : 1;
        uint32_t ya = sb + (isB ? OFF_K : OFF_U) + (8 * (rr >> 1) + 2 * ti + (rr & 1)) * 128 + (rr ^ G) * 16;
        uint32_t ya2 = sb + OFF_K + (32 + 8 * ((rr >> 1) & 1) + 2 * ti + (rr & 1)) * 128 + ((rr >> 2) ^ (2 * (rr & 3)) ^ G) * 16;
        uint32_t oa = sb + (isB ? OFF_V : OFF_TAB) + row0 * 64 + c * 16, oa2 = sb + OFF_V + 4096 + row2 * 32 + (c & 1) * 16;
        uint4* go = (uint4*)(P.out + (size_t)(64 * rank + row0) * 1152 + (isB ? 576 : 0) + ch0 + c * 8);
        uint4* go2 = (uint4*)(P.out + (size_t)(64 * rank + row2) * 1152 + 576 + ch0 + 32 + (c & 1) * 8);
#pragma unroll 1
        for (uint32_t e = 0; e < 8; e++) {
            bar_wait(bars + (BAR_Y + e) * 8);
            MARK(10 + e); MK2(10 + e);
            uint32_t y0[4], y1[4];
            ldsm4t(y0, ya); ldsm4t(y1, ya ^ 16);
            if (isB) {
                uint32_t y2[4];
                ldsm4t(y2, ya2);
                const uint4 q0 = lds128(oa), q1 = lds128(oa + rd * 64), q2 = lds128(oa2);
                y0[0] = bmul(y0[0], q0.x); y0[1] = bmul(y0[1], q0.y); y0[2] = bmul(y0[2], q0.z); y0[3] = bmul(y0[3], q0.w);
                y1[0] = bmul(y1[0], q1.x); y1[1] = bmul(y1[1], q1.y); y1[2] = bmul(y1[2], q1.z); y1[3] = bmul(y1[3], q1.w);
                *go2 = make_uint4(bmul(y2[0], q2.x), bmul(y2[1], q2.y), bmul(y2[2], q2.z), bmul(y2[3], q2.w));
            }
            go[0] = make_uint4(y0[0], y0[1], y0[2], y0[3]);
            go[rd * 144] = make_uint4(y1[0], y1[1], y1[2], y1[3]);
            go += 256 * 144; go2 += 256 * 144;
            ya += isB ? KP : UP; ya2 += KP; oa += isB ? VP : 4096; oa2 += VP;
        }

    }
    MARK_END();
    asm volatile("pmevent 0;");
}

typedef CUresult (*EncodeFn)(CUtensorMap*, CUtensorMapDataType, cuuint32_t, void*, const cuuint64_t*, const cuuint64_t*, const cuuint32_t*,
                             const cuuint32_t*, CUtensorMapInterleave, CUtensorMapSwizzle, CUtensorMapL2promotion, CUtensorMapFloatOOBfill);
static void enc3(EncodeFn f, CUtensorMap* m, void* p, uint32_t b0, uint32_t b1, uint32_t b2) {
    cuuint64_t gd[3] = {576, 16, 128}, gs[2] = {1152, 18432};
    cuuint32_t bd[3] = {b0, b1, b2}, es[3] = {1, 1, 1};
    f(m, CU_TENSOR_MAP_DATA_TYPE_BFLOAT16, 3, p, gd, gs, bd, es, CU_TENSOR_MAP_INTERLEAVE_NONE, CU_TENSOR_MAP_SWIZZLE_NONE,
      PROMO, CU_TENSOR_MAP_FLOAT_OOB_FILL_NONE);
}
static void enc2(EncodeFn f, CUtensorMap* m, void* p, uint32_t width, uint32_t b0) {
    cuuint64_t gd[2] = {width, 2048}, gs[1] = {(cuuint64_t)width * 2};
    cuuint32_t bd[2] = {b0, 64}, es[2] = {1, 1};
    f(m, CU_TENSOR_MAP_DATA_TYPE_BFLOAT16, 2, p, gd, gs, bd, es, CU_TENSOR_MAP_INTERLEAVE_NONE, CU_TENSOR_MAP_SWIZZLE_NONE,
      PROMO, CU_TENSOR_MAP_FLOAT_OOB_FILL_NONE);
}

extern "C" void kernel_launch(void* const* d_in, const int* in_sizes, int n_in, void* d_out, int out_size) {
    static EncodeFn enc = nullptr;
    static void* frag = nullptr;
    if (!enc) {
        void* fn = nullptr;
        cudaDriverEntryPointQueryResult q;
        cudaGetDriverEntryPoint("cuTensorMapEncodeTiled", &fn, cudaEnableDefault, &q);
        enc = (EncodeFn)fn;
        cudaGetSymbolAddress(&frag, g_frag);
        cudaFuncSetAttribute(ssm_conv_kernel, cudaFuncAttributeMaxDynamicSharedMemorySize, SMEM_BYTES + TRACE_BYTES);
    }
    Maps M;
    enc3(enc, &M.u, d_in[0], 32, 17, 4);
    enc3(enc, &M.k, d_in[10], 48, 17, 4);
    enc3(enc, &M.kh, d_in[10], 48, 4, 1);
    enc3(enc, &M.v, d_in[11], 48, 17, 4);
    enc2(enc, &M.q32, d_in[9], 576, 32);
    enc2(enc, &M.q16, d_in[9], 576, 16);
    enc2(enc, &M.o32, d_out, 1152, 32);
    enc2(enc, &M.o16, d_out, 1152, 16);
    Ptrs P;
    P.are = (const uint16_t*)d_in[1]; P.aim = (const uint16_t*)d_in[2]; P.bre = (const uint16_t*)d_in[3]; P.bim = (const uint16_t*)d_in[4];
    P.cre = (const uint16_t*)d_in[5]; P.cim = (const uint16_t*)d_in[6]; P.logdt = (const uint16_t*)d_in[7]; P.dskip = (const uint16_t*)d_in[8];
    P.shiftk = (const uint16_t*)d_in[12]; P.ssmk = (const uint16_t*)d_in[13]; P.ssmd = (const uint16_t*)d_in[14]; P.out = (uint16_t*)d_out; P.frag = (const uint32_t*)frag;
    ssm_conv_kernel<<<NCTA, 512, SMEM_BYTES + TRACE_BYTES, cudaStreamPerThread>>>(P, M);
}
```
